```python
import torch

def _softmax(x, axis=-1):
    return torch.softmax(x, dim=axis)
def _gelu(x):
    return torch.nn.functional.gelu(x, approximate="tanh")
def _silu(x):
    return torch.nn.functional.silu(x)
def _sigmoid(x):
    return torch.sigmoid(x)
def _layernorm(x, axis=-1, eps=1e-5):
    m = x.mean(dim=axis, keepdim=True)
    v = x.var(dim=axis, keepdim=True, unbiased=False)
    return (x - m) / torch.sqrt(v + eps)
def _scatter_add(tgt, idx, src, axis=0):
    return tgt.clone().index_add_(axis, idx, src)
def _segment_sum(src, seg, n):
    out = torch.zeros((n,) + src.shape[1:], dtype=src.dtype)
    return out.index_add_(0, seg, src)
def _pad(x, pw):
    flat = tuple(v for pair in reversed(pw) for v in pair)
    return torch.nn.functional.pad(x, flat)

kernel_name = 'concat_heads__grouped_kv_mqa__mha_block__prompt'

def setup_inputs():

    _w = (lambda a: (lambda t: t.to(torch.bfloat16) if t.is_floating_point() else t)(torch.as_tensor(a)))
    def _A_setup():
        B, S, D, H = 1, 2048, 1024, 32
        Dh = D // H
        return {
            "x": _w((lambda *s: torch.randn(*s, dtype=torch.bfloat16) * 0.05)(B, S, D)),
            "wq": _w((lambda *s: torch.randn(*s, dtype=torch.bfloat16) * 0.8)(D, H * Dh)),
            "wk": _w((lambda *s: torch.randn(*s, dtype=torch.bfloat16) * 0.8)(D, Dh)),
            "wv": _w((lambda *s: torch.randn(*s, dtype=torch.bfloat16) * 0.1)(D, Dh)),
            "wo": _w((lambda *s: torch.randn(*s, dtype=torch.bfloat16) * 0.1)(H * Dh, D)),
        }
    _A_in = _A_setup()

    def _B_setup():
        B, S, D, H = 1, 2048, 1024, 32
        return {
            "x": _w((lambda *s: torch.randn(*s, dtype=torch.bfloat16) * 0.2)(B, S, D)),
            "wqkv": _w((lambda *s: torch.randn(*s, dtype=torch.bfloat16) * 0.2)(D, 3 * D)),
            "wo": _w((lambda *s: torch.randn(*s, dtype=torch.bfloat16) * 0.05)(D, D)),
        }
    _B_in = _B_setup()

    return {
        "A_x": _A_in["x"],
        "A_wq": _A_in["wq"],
        "A_wk": _A_in["wk"],
        "A_wv": _A_in["wv"],
        "A_wo": _A_in["wo"],
        "B_x": _B_in["x"],
        "B_wqkv": _B_in["wqkv"],
        "B_wo": _B_in["wo"],
    }

def reference(A_x, A_wq, A_wk, A_wv, A_wo, B_x, B_wqkv, B_wo):
    def _A_ref(x, wq, wk, wv, wo):
        B, S, D = x.shape
        H = 32
        Dh = D // H
        q = (lambda x, *d: x.permute(*d))((x @ wq).reshape(B, S, H, Dh), 0, 2, 1, 3)
        k = x @ wk
        v = x @ wv
        scores = torch.einsum("bhqd,bkd->bhqk", q, k) * (Dh ** -0.5)
        p = _softmax(scores, axis=-1)
        o = torch.einsum("bhqk,bkd->bhqd", p, v)
        return (lambda x, *d: x.permute(*d))(o, 0, 2, 1, 3).reshape(B, S, H * Dh) @ wo

    def _B_ref(x, wqkv, wo):
        B, S, D = x.shape
        H = 32
        Dh = D // H
        qkv = (lambda x, *d: x.permute(*d))((x @ wqkv).reshape(B, S, 3, H, Dh), 2, 0, 3, 1, 4)
        q, k, v = qkv[0], qkv[1], qkv[2]
        scores = torch.einsum("bhqd,bhkd->bhqk", q, k) * (Dh ** -0.5)
        p = _softmax(scores, axis=-1)
        o = torch.einsum("bhqk,bhkd->bhqd", p, v)
        return (lambda x, *d: x.permute(*d))(o, 0, 2, 1, 3).reshape(B, S, D) @ wo

    a = _A_ref(A_x, A_wq, A_wk, A_wv, A_wo)
    b = _B_ref(B_x, B_wqkv, B_wo)
    return torch.concatenate([a, b], axis=-1)
```

```cpp
#include <cuda_runtime.h>
#include <cuda_bf16.h>
#include <cuda.h>
#include <stdint.h>

constexpr int SEQ = 2048;

__device__ __align__(1024) uint4 g_Q[64 * SEQ * 4];
__device__ __align__(1024) uint4 g_K[33 * SEQ * 4];
__device__ __align__(1024) uint4 g_V[33 * SEQ * 4];
__device__ __align__(1024) uint4 g_O[2 * SEQ * 128];
__device__ __align__(16) float g_nrm[130 * 128];

__device__ __forceinline__ void wgmma_rs_n40_t1(float (&d)[20], uint32_t a0, uint32_t a1, uint32_t a2, uint32_t a3, uint64_t descB, int scaleD) {
    asm volatile("{\n.reg .pred p;\nsetp.ne.b32 p, %25, 0;\n"
        "wgmma.mma_async.sync.aligned.m64n40k16.f32.bf16.bf16 "
        "{%0, %1, %2, %3, %4, %5, %6, %7, %8, %9, %10, %11, %12, %13, %14, %15, "
        "%16, %17, %18, %19}, "
        "{%20, %21, %22, %23}, %24, p, 1, 1, 1;\n}\n"
        : "+f"(d[0]), "+f"(d[1]), "+f"(d[2]), "+f"(d[3]), "+f"(d[4]), "+f"(d[5]), "+f"(d[6]), "+f"(d[7]),
          "+f"(d[8]), "+f"(d[9]), "+f"(d[10]), "+f"(d[11]), "+f"(d[12]), "+f"(d[13]), "+f"(d[14]), "+f"(d[15]),
          "+f"(d[16]), "+f"(d[17]), "+f"(d[18]), "+f"(d[19])
        : "r"(a0), "r"(a1), "r"(a2), "r"(a3), "l"(descB), "r"(scaleD));
}
__device__ __forceinline__ void wgmma_rs_n64_t0(float (&d)[32], uint32_t a0, uint32_t a1, uint32_t a2, uint32_t a3, uint64_t descB, int scaleD) {
    asm volatile("{\n.reg .pred p;\nsetp.ne.b32 p, %37, 0;\n"
        "wgmma.mma_async.sync.aligned.m64n64k16.f32.bf16.bf16 "
        "{%0, %1, %2, %3, %4, %5, %6, %7, %8, %9, %10, %11, %12, %13, %14, %15, "
        "%16, %17, %18, %19, %20, %21, %22, %23, %24, %25, %26, %27, %28, %29, %30, %31}, "
        "{%32, %33, %34, %35}, %36, p, 1, 1, 0;\n}\n"
        : "+f"(d[0]), "+f"(d[1]), "+f"(d[2]), "+f"(d[3]), "+f"(d[4]), "+f"(d[5]), "+f"(d[6]), "+f"(d[7]),
          "+f"(d[8]), "+f"(d[9]), "+f"(d[10]), "+f"(d[11]), "+f"(d[12]), "+f"(d[13]), "+f"(d[14]), "+f"(d[15]),
          "+f"(d[16]), "+f"(d[17]), "+f"(d[18]), "+f"(d[19]), "+f"(d[20]), "+f"(d[21]), "+f"(d[22]), "+f"(d[23]),
          "+f"(d[24]), "+f"(d[25]), "+f"(d[26]), "+f"(d[27]), "+f"(d[28]), "+f"(d[29]), "+f"(d[30]), "+f"(d[31])
        : "r"(a0), "r"(a1), "r"(a2), "r"(a3), "l"(descB), "r"(scaleD));
}
__device__ __forceinline__ void wgmma_ss_n256_t1(float (&d)[128], uint64_t descA, uint64_t descB, int scaleD) {
    asm volatile("{\n.reg .pred p;\nsetp.ne.b32 p, %130, 0;\n"
        "wgmma.mma_async.sync.aligned.m64n256k16.f32.bf16.bf16 "
        "{%0, %1, %2, %3, %4, %5, %6, %7, %8, %9, %10, %11, %12, %13, %14, %15, "
        "%16, %17, %18, %19, %20, %21, %22, %23, %24, %25, %26, %27, %28, %29, %30, %31, "
        "%32, %33, %34, %35, %36, %37, %38, %39, %40, %41, %42, %43, %44, %45, %46, %47, "
        "%48, %49, %50, %51, %52, %53, %54, %55, %56, %57, %58, %59, %60, %61, %62, %63, "
        "%64, %65, %66, %67, %68, %69, %70, %71, %72, %73, %74, %75, %76, %77, %78, %79, "
        "%80, %81, %82, %83, %84, %85, %86, %87, %88, %89, %90, %91, %92, %93, %94, %95, "
        "%96, %97, %98, %99, %100, %101, %102, %103, %104, %105, %106, %107, %108, %109, %110, %111, "
        "%112, %113, %114, %115, %116, %117, %118, %119, %120, %121, %122, %123, %124, %125, %126, %127}, "
        "%128, %129, p, 1, 1, 0, 1;\n}\n"
        : "+f"(d[0]), "+f"(d[1]), "+f"(d[2]), "+f"(d[3]), "+f"(d[4]), "+f"(d[5]), "+f"(d[6]), "+f"(d[7]),
          "+f"(d[8]), "+f"(d[9]), "+f"(d[10]), "+f"(d[11]), "+f"(d[12]), "+f"(d[13]), "+f"(d[14]), "+f"(d[15]),
          "+f"(d[16]), "+f"(d[17]), "+f"(d[18]), "+f"(d[19]), "+f"(d[20]), "+f"(d[21]), "+f"(d[22]), "+f"(d[23]),
          "+f"(d[24]), "+f"(d[25]), "+f"(d[26]), "+f"(d[27]), "+f"(d[28]), "+f"(d[29]), "+f"(d[30]), "+f"(d[31]),
          "+f"(d[32]), "+f"(d[33]), "+f"(d[34]), "+f"(d[35]), "+f"(d[36]), "+f"(d[37]), "+f"(d[38]), "+f"(d[39]),
          "+f"(d[40]), "+f"(d[41]), "+f"(d[42]), "+f"(d[43]), "+f"(d[44]), "+f"(d[45]), "+f"(d[46]), "+f"(d[47]),
          "+f"(d[48]), "+f"(d[49]), "+f"(d[50]), "+f"(d[51]), "+f"(d[52]), "+f"(d[53]), "+f"(d[54]), "+f"(d[55]),
          "+f"(d[56]), "+f"(d[57]), "+f"(d[58]), "+f"(d[59]), "+f"(d[60]), "+f"(d[61]), "+f"(d[62]), "+f"(d[63]),
          "+f"(d[64]), "+f"(d[65]), "+f"(d[66]), "+f"(d[67]), "+f"(d[68]), "+f"(d[69]), "+f"(d[70]), "+f"(d[71]),
          "+f"(d[72]), "+f"(d[73]), "+f"(d[74]), "+f"(d[75]), "+f"(d[76]), "+f"(d[77]), "+f"(d[78]), "+f"(d[79]),
          "+f"(d[80]), "+f"(d[81]), "+f"(d[82]), "+f"(d[83]), "+f"(d[84]), "+f"(d[85]), "+f"(d[86]), "+f"(d[87]),
          "+f"(d[88]), "+f"(d[89]), "+f"(d[90]), "+f"(d[91]), "+f"(d[92]), "+f"(d[93]), "+f"(d[94]), "+f"(d[95]),
          "+f"(d[96]), "+f"(d[97]), "+f"(d[98]), "+f"(d[99]), "+f"(d[100]), "+f"(d[101]), "+f"(d[102]), "+f"(d[103]),
          "+f"(d[104]), "+f"(d[105]), "+f"(d[106]), "+f"(d[107]), "+f"(d[108]), "+f"(d[109]), "+f"(d[110]), "+f"(d[111]),
          "+f"(d[112]), "+f"(d[113]), "+f"(d[114]), "+f"(d[115]), "+f"(d[116]), "+f"(d[117]), "+f"(d[118]), "+f"(d[119]),
          "+f"(d[120]), "+f"(d[121]), "+f"(d[122]), "+f"(d[123]), "+f"(d[124]), "+f"(d[125]), "+f"(d[126]), "+f"(d[127])
        : "l"(descA), "l"(descB), "r"(scaleD));
}
__device__ __forceinline__ void wgmma_ss_n64_t1(float (&d)[32], uint64_t descA, uint64_t descB, int scaleD) {
    asm volatile("{\n.reg .pred p;\nsetp.ne.b32 p, %34, 0;\n"
        "wgmma.mma_async.sync.aligned.m64n64k16.f32.bf16.bf16 "
        "{%0, %1, %2, %3, %4, %5, %6, %7, %8, %9, %10, %11, %12, %13, %14, %15, "
        "%16, %17, %18, %19, %20, %21, %22, %23, %24, %25, %26, %27, %28, %29, %30, %31}, "
        "%32, %33, p, 1, 1, 0, 1;\n}\n"
        : "+f"(d[0]), "+f"(d[1]), "+f"(d[2]), "+f"(d[3]), "+f"(d[4]), "+f"(d[5]), "+f"(d[6]), "+f"(d[7]),
          "+f"(d[8]), "+f"(d[9]), "+f"(d[10]), "+f"(d[11]), "+f"(d[12]), "+f"(d[13]), "+f"(d[14]), "+f"(d[15]),
          "+f"(d[16]), "+f"(d[17]), "+f"(d[18]), "+f"(d[19]), "+f"(d[20]), "+f"(d[21]), "+f"(d[22]), "+f"(d[23]),
          "+f"(d[24]), "+f"(d[25]), "+f"(d[26]), "+f"(d[27]), "+f"(d[28]), "+f"(d[29]), "+f"(d[30]), "+f"(d[31])
        : "l"(descA), "l"(descB), "r"(scaleD));
}

__device__ __forceinline__ void wg_fence() { asm volatile("wgmma.fence.sync.aligned;" ::: "memory"); }
__device__ __forceinline__ void wg_commit() { asm volatile("wgmma.commit_group.sync.aligned;" ::: "memory"); }
template <int N> __device__ __forceinline__ void wg_wait() { asm volatile("wgmma.wait_group.sync.aligned %0;" ::"n"(N) : "memory"); }
template <int N> __device__ __forceinline__ void pin(float (&r)[N]) {
#pragma unroll
    for (int i = 0; i < N; i++) asm volatile("" : "+f"(r[i])::"memory");
}
template <int N> __device__ __forceinline__ void pin(uint32_t (&r)[N]) {
#pragma unroll
    for (int i = 0; i < N; i++) asm volatile("" : "+r"(r[i])::"memory");
}
__device__ __forceinline__ uint64_t mkdesc(uint32_t addr, uint32_t lbo, uint32_t sbo, int swz) {
    return (uint64_t)((addr & 0x3FFFF) >> 4) | ((uint64_t)((lbo >> 4) & 0x3FFF) << 16) | ((uint64_t)((sbo >> 4) & 0x3FFF) << 32) | ((uint64_t)swz << 62);
}
__device__ __forceinline__ uint32_t smem_u32(const void* p) { return (uint32_t)__cvta_generic_to_shared(p); }
__device__ __forceinline__ void mbar_init(uint32_t bar, uint32_t cnt) { asm volatile("mbarrier.init.shared::cta.b64 [%0], %1;" ::"r"(bar), "r"(cnt) : "memory"); }
__device__ __forceinline__ void mbar_arrive(uint32_t bar) { asm volatile("mbarrier.arrive.shared::cta.b64 _, [%0];" ::"r"(bar) : "memory"); }
__device__ __forceinline__ void mbar_arrive_cluster(uint32_t bar) { asm volatile("mbarrier.arrive.shared::cluster.b64 _, [%0];" ::"r"(bar) : "memory"); }
__device__ __forceinline__ void mbar_expect_tx(uint32_t bar, uint32_t bytes) { asm volatile("mbarrier.arrive.expect_tx.shared::cta.b64 _, [%0], %1;" ::"r"(bar), "r"(bytes) : "memory"); }
__device__ __forceinline__ void mbar_wait(uint32_t bar, uint32_t parity) {
    asm volatile("{\n.reg .pred p;\n.reg .u32 cnt;\nmov.u32 cnt, 0;\nLAB_WAIT:\n"
                 "mbarrier.try_wait.parity.shared::cta.b64 p, [%0], %1;\n"
                 "@p bra LAB_DONE;\n"
                 "add.u32 cnt, cnt, 1;\n"
                 "setp.lt.u32 p, cnt, 0x1000000;\n"
                 "@p bra LAB_WAIT;\n"
                 "trap;\n"
                 "LAB_DONE:\n}\n" ::"r"(bar), "r"(parity) : "memory");
}
__device__ __forceinline__ uint32_t mapa(uint32_t addr, uint32_t rank) { uint32_t r; asm("mapa.shared::cluster.u32 %0, %1, %2;" : "=r"(r) : "r"(addr), "r"(rank)); return r; }
__device__ __forceinline__ void bulk_g2s(uint32_t dst, const void* src, uint32_t bytes, uint32_t bar) {
    asm volatile("cp.async.bulk.shared::cluster.global.mbarrier::complete_tx::bytes [%0], [%1], %2, [%3];" ::"r"(dst), "l"(src), "r"(bytes), "r"(bar) : "memory");
}
__device__ __forceinline__ void tma_ld(uint32_t dst, const CUtensorMap* m, int x, int y, uint32_t bar) {
    asm volatile("cp.async.bulk.tensor.2d.shared::cluster.global.mbarrier::complete_tx::bytes [%0], [%1, {%3, %4}], [%2];" ::"r"(dst), "l"(m), "r"(bar), "r"(x), "r"(y) : "memory");
}
__device__ __forceinline__ void tma_ld_mc(uint32_t dst, const CUtensorMap* m, int x, int y, uint32_t bar, uint16_t mask) {
    asm volatile("cp.async.bulk.tensor.2d.shared::cluster.global.mbarrier::complete_tx::bytes.multicast::cluster [%0], [%1, {%3, %4}], [%2], %5;" ::"r"(dst), "l"(m), "r"(bar), "r"(x), "r"(y), "h"(mask) : "memory");
}
__device__ __forceinline__ void tma_st(const CUtensorMap* m, uint32_t src, int x, int y) {
    asm volatile("cp.async.bulk.tensor.2d.global.shared::cta.bulk_group [%0, {%2, %3}], [%1];" ::"l"(m), "r"(src), "r"(x), "r"(y) : "memory");
}
__device__ __forceinline__ void prefetch_tmap(const CUtensorMap* m) { asm volatile("prefetch.tensormap [%0];" ::"l"(m) : "memory"); }
__device__ __forceinline__ void pdl_wait() { asm volatile("griddepcontrol.wait;" ::: "memory"); }
__device__ __forceinline__ void pdl_launch() { asm volatile("griddepcontrol.launch_dependents;" ::: "memory"); }
__device__ __forceinline__ void cluster_sync() { asm volatile("barrier.cluster.arrive.release.aligned;\nbarrier.cluster.wait.acquire.aligned;" ::: "memory"); }
__device__ __forceinline__ float ex2f(float x) { float y; asm("ex2.approx.ftz.f32 %0, %1;" : "=f"(y) : "f"(x)); return y; }
__device__ __forceinline__ uint32_t pack_bf16(float lo, float hi) { uint32_t r; asm("cvt.rn.bf16x2.f32 %0, %1, %2;" : "=r"(r) : "f"(hi), "f"(lo)); return r; }
template <int R> __device__ __forceinline__ void reg_inc() { asm volatile("setmaxnreg.inc.sync.aligned.u32 %0;" ::"n"(R)); }
template <int R> __device__ __forceinline__ void reg_dec() { asm volatile("setmaxnreg.dec.sync.aligned.u32 %0;" ::"n"(R)); }

constexpr int G_ST = 4;
constexpr int G_STAGE = 49152;
constexpr int G_SMEM = G_ST * G_STAGE + 1024 + 128;

__device__ __forceinline__ void gemm_mainloop(float (&acc)[128], uint32_t sb, uint32_t bars, int wg, uint32_t relbar, uint32_t& ph, bool last_tile) {
#pragma unroll 1
    for (int kb = 0; kb < 16; kb++) {
        int s = kb & 3;
        mbar_wait(bars + 16 * s, ph);
        if (s == 3) ph ^= 1;
        uint64_t da = mkdesc(sb + s * G_STAGE + wg * 8192, 16, 1024, 1);
        uint64_t db = mkdesc(sb + s * G_STAGE + 16384, 8192, 1024, 1);
        wg_fence();
#pragma unroll
        for (int k = 0; k < 4; k++) wgmma_ss_n256_t1(acc, da + 2 * k, db + 128 * k, (k > 0) ? 1 : kb);
        wg_commit();
        wg_wait<1>();
        if (kb > 0 && relbar && !(last_tile && kb > 12)) mbar_arrive_cluster(relbar + 16 * ((kb - 1) & 3));
    }
    wg_wait<0>();
    pin(acc);
    if (relbar && !last_tile) mbar_arrive_cluster(relbar + 16 * 3);
}

__device__ __forceinline__ float shx(float v, int m) { return __shfl_xor_sync(0xffffffffu, v, m); }

__global__ void __cluster_dims__(2, 1, 1) __launch_bounds__(384, 1)
proj_kernel(const __grid_constant__ CUtensorMap mXA, const __grid_constant__ CUtensorMap mXB, const __grid_constant__ CUtensorMap mWq,
            const __grid_constant__ CUtensorMap mWqkv, const __grid_constant__ CUtensorMap mWk, const __grid_constant__ CUtensorMap mWv) {
    extern __shared__ uint8_t smem_raw[];
    const uint32_t sb = (smem_u32(smem_raw) + 1023) & ~1023u;
    const uint32_t bars = sb + G_ST * G_STAGE;
    const int tid = threadIdx.x, wg = tid >> 7;
    const int cid = blockIdx.x >> 1, rank = blockIdx.x & 1;
    const bool small = cid >= 64;
    if (tid == 256) {
        for (int s = 0; s < G_ST; s++) { mbar_init(bars + 16 * s, 1); mbar_init(bars + 16 * s + 8, small ? 8 : 16); }
        asm volatile("fence.mbarrier_init.release.cluster;" ::: "memory");
        prefetch_tmap(&mXA); prefetch_tmap(&mXB); prefetch_tmap(&mWq); prefetch_tmap(&mWqkv);
    }
    cluster_sync();
    pdl_launch();
    const int mblk = 2 * (cid & 7) + rank;
    const int nb = (cid >> 3) & 3;
    if (wg == 2) {
        reg_dec<40>();
        if (tid == 256) {
            uint32_t ph = 1;
            if (!small) {
                for (int w = 0; w < 2; w++) {
                    const bool isA = (w == 0 && cid < 32);
                    const CUtensorMap* ma = isA ? &mXA : &mXB;
                    const CUtensorMap* mb = isA ? &mWq : &mWqkv;
                    const int n0 = (cid < 32 ? nb : (w == 0 ? 4 + nb : 8 + nb)) * 256 + rank * 128;
                    for (int kb = 0; kb < 16; kb++) {
                        int s = kb & 3;
                        uint32_t fb = bars + 16 * s, st = sb + s * G_STAGE;
                        mbar_wait(fb + 8, ph);
                        if (s == 3) ph ^= 1;
                        mbar_expect_tx(fb, G_STAGE);
                        tma_ld(st, ma, kb * 64, mblk * 128, fb);
                        tma_ld_mc(st + 16384 + rank * 16384, mb, n0, kb * 64, fb, 3);
                        tma_ld_mc(st + 16384 + rank * 16384 + 8192, mb, n0 + 64, kb * 64, fb, 3);
                    }
                }
            } else {
                const int r0 = (blockIdx.x - 128) * 512;
                for (int w = 0; w < 2; w++)
                    for (int kb = 0; kb < 16; kb++) {
                        int s = kb & 3;
                        uint32_t fb = bars + 16 * s, st = sb + s * G_STAGE;
                        mbar_wait(fb + 8, ph);
                        if (s == 3) ph ^= 1;
                        mbar_expect_tx(fb, 40960);
                        tma_ld(st, &mXA, kb * 64, r0 + w * 256, fb);
                        tma_ld(st + 16384, &mXA, kb * 64, r0 + w * 256 + 128, fb);
                        tma_ld(st + 32768, &mWk, 0, kb * 64, fb);
                        tma_ld(st + 36864, &mWv, 0, kb * 64, fb);
                    }
            }
        }
    } else {
        reg_inc<232>();
        const int lane = tid & 31, warp = (tid >> 5) & 3, g = lane >> 2, c = lane & 3;
        uint32_t ph = 0;
        if (!small) {
            const uint32_t relbar = lane < 2 ? mapa(bars + 8, lane) : 0;
            float acc[128];
#pragma unroll 1
            for (int w = 0; w < 2; w++) {
                gemm_mainloop(acc, sb, bars, wg, relbar, ph, w == 1);
                const bool isQ = cid < 32;
                const int row = mblk * 128 + wg * 64 + warp * 16 + g;
                uint4* dst; int slot;
                if (isQ) { slot = w * 32 + nb * 8; dst = g_Q + (size_t)slot * SEQ * 4; }
                else { slot = 1 + nb * 8; dst = (w == 0 ? g_K : g_V) + (size_t)slot * SEQ * 4; slot += (w == 0 ? 64 : 97); }
                dst += row * 4 + (isQ ? c : (c ^ ((row >> 1) & 3)));
                const float sc = isQ ? 0.25503486f : 1.0f;
                float ss[16];
#pragma unroll
                for (int h = 0; h < 8; h++) {
                    float v[16];
#pragma unroll
                    for (int i = 0; i < 16; i++) v[i] = acc[16 * h + i] * sc;
                    dst[h * SEQ * 4] = make_uint4(pack_bf16(v[0], v[1]), pack_bf16(v[4], v[5]), pack_bf16(v[8], v[9]), pack_bf16(v[12], v[13]));
                    dst[h * SEQ * 4 + 32] = make_uint4(pack_bf16(v[2], v[3]), pack_bf16(v[6], v[7]), pack_bf16(v[10], v[11]), pack_bf16(v[14], v[15]));
                    float a = 0.f, b = 0.f;
#pragma unroll
                    for (int j = 0; j < 4; j++) {
                        a = fmaf(v[4 * j], v[4 * j], fmaf(v[4 * j + 1], v[4 * j + 1], a));
                        b = fmaf(v[4 * j + 2], v[4 * j + 2], fmaf(v[4 * j + 3], v[4 * j + 3], b));
                    }
                    ss[h] = a; ss[8 + h] = b;
                }
                float t8[8], t4[4];
#pragma unroll
                for (int h = 0; h < 8; h++) t8[h] = ((c & 1) ? ss[8 + h] : ss[h]) + shx((c & 1) ? ss[h] : ss[8 + h], 1);
#pragma unroll
                for (int h = 0; h < 4; h++) t4[h] = ((c & 2) ? t8[4 + h] : t8[h]) + shx((c & 2) ? t8[h] : t8[4 + h], 2);
                uint32_t u2[2], u1;
#pragma unroll
                for (int h = 0; h < 2; h++) u2[h] = max(__float_as_uint((c & 1) ? t4[2 + h] : t4[h]), __float_as_uint(shx((c & 1) ? t4[h] : t4[2 + h], 1)));
                u1 = max((g & 1) ? u2[1] : u2[0], __shfl_xor_sync(0xffffffffu, (g & 1) ? u2[0] : u2[1], 4));
                u1 = max(u1, __shfl_xor_sync(0xffffffffu, u1, 8));
                u1 = max(u1, __shfl_xor_sync(0xffffffffu, u1, 16));
                if (g < 2) g_nrm[(slot + (c >> 1) * 4 + (c & 1) * 2 + g) * 128 + (row >> 4)] = __uint_as_float(u1);
            }
        } else {
            float acc[2][32];
#pragma unroll 1
            for (int w = 0; w < 2; w++) {
#pragma unroll 1
                for (int kb = 0; kb < 16; kb++) {
                    int s = kb & 3;
                    mbar_wait(bars + 16 * s, ph);
                    if (s == 3) ph ^= 1;
                    uint64_t da = mkdesc(sb + s * G_STAGE + wg * 16384, 16, 1024, 1);
                    uint64_t db = mkdesc(sb + s * G_STAGE + 32768, 4096, 512, 2);
                    wg_fence();
#pragma unroll
                    for (int k = 0; k < 4; k++) {
                        wgmma_ss_n64_t1(acc[0], da + 2 * k, db + 64 * k, (k > 0) ? 1 : kb);
                        wgmma_ss_n64_t1(acc[1], da + 512 + 2 * k, db + 64 * k, (k > 0) ? 1 : kb);
                    }
                    wg_commit();
                    wg_wait<0>();
                    if (lane == 0) mbar_arrive(bars + 16 * s + 8);
                }
                pin(acc[0]); pin(acc[1]);
#pragma unroll
                for (int m = 0; m < 2; m++) {
                    const int row = (blockIdx.x - 128) * 512 + w * 256 + wg * 128 + m * 64 + warp * 16 + g;
                    const int off = row * 4 + (c ^ ((row >> 1) & 3));
#pragma unroll
                    for (int h = 0; h < 2; h++) {
                        const float* v = &acc[m][16 * h];
                        uint4* dst = (h == 0 ? g_K : g_V) + off;
                        dst[0] = make_uint4(pack_bf16(v[0], v[1]), pack_bf16(v[4], v[5]), pack_bf16(v[8], v[9]), pack_bf16(v[12], v[13]));
                        dst[32] = make_uint4(pack_bf16(v[2], v[3]), pack_bf16(v[6], v[7]), pack_bf16(v[10], v[11]), pack_bf16(v[14], v[15]));
                        float a = 0.f, b = 0.f;
#pragma unroll
                        for (int j = 0; j < 4; j++) {
                            a = fmaf(v[4 * j], v[4 * j], fmaf(v[4 * j + 1], v[4 * j + 1], a));
                            b = fmaf(v[4 * j + 2], v[4 * j + 2], fmaf(v[4 * j + 3], v[4 * j + 3], b));
                        }
                        a += shx(a, 1); b += shx(b, 1);
                        a += shx(a, 2); b += shx(b, 2);
                        uint32_t u = __reduce_max_sync(0xffffffffu, max(__float_as_uint(a), __float_as_uint(b)));
                        if (lane == 0) g_nrm[(h == 0 ? 64 : 97) * 128 + (row >> 4)] = __uint_as_float(u);
                    }
                }
            }
        }
    }
}

__global__ void __cluster_dims__(2, 1, 1) __launch_bounds__(384, 1)
outproj_kernel(const __grid_constant__ CUtensorMap mO, const __grid_constant__ CUtensorMap mWoA, const __grid_constant__ CUtensorMap mWoB,
               const __grid_constant__ CUtensorMap mOut) {
    extern __shared__ uint8_t smem_raw[];
    const uint32_t sb = (smem_u32(smem_raw) + 1023) & ~1023u;
    const uint32_t bars = sb + G_ST * G_STAGE;
    const int tid = threadIdx.x, wg = tid >> 7;
    const int cid = blockIdx.x >> 1, rank = blockIdx.x & 1;
    const int br = cid >> 5, nb = (cid >> 3) & 3, mblk = 2 * (cid & 7) + rank;
    if (tid == 256) {
        for (int s = 0; s < G_ST; s++) { mbar_init(bars + 16 * s, 1); mbar_init(bars + 16 * s + 8, 16); }
        asm volatile("fence.mbarrier_init.release.cluster;" ::: "memory");
        prefetch_tmap(&mO); prefetch_tmap(br ? &mWoB : &mWoA); prefetch_tmap(&mOut);
    }
    cluster_sync();
    if (wg == 2) {
        reg_dec<40>();
        if (tid == 256) {
            const CUtensorMap* mb = br ? &mWoB : &mWoA;
            const int n0 = nb * 256 + rank * 128, r0 = br * SEQ + mblk * 128;
            for (int s = 0; s < G_ST; s++) {
                uint32_t fb = bars + 16 * s, st = sb + s * G_STAGE;
                mbar_expect_tx(fb, G_STAGE);
                tma_ld_mc(st + 16384 + rank * 16384, mb, n0, s * 64, fb, 3);
                tma_ld_mc(st + 16384 + rank * 16384 + 8192, mb, n0 + 64, s * 64, fb, 3);
            }
            pdl_wait();
            for (int s = 0; s < G_ST; s++) tma_ld(sb + s * G_STAGE, &mO, s * 64, r0, bars + 16 * s);
            uint32_t ph = 0;
            for (int kb = 4; kb < 16; kb++) {
                int s = kb & 3;
                uint32_t fb = bars + 16 * s, st = sb + s * G_STAGE;
                mbar_wait(fb + 8, ph);
                if (s == 3) ph ^= 1;
                mbar_expect_tx(fb, G_STAGE);
                tma_ld(st, &mO, kb * 64, r0, fb);
                tma_ld_mc(st + 16384 + rank * 16384, mb, n0, kb * 64, fb, 3);
                tma_ld_mc(st + 16384 + rank * 16384 + 8192, mb, n0 + 64, kb * 64, fb, 3);
            }
        }
    } else {
        reg_inc<232>();
        const int lane = tid & 31, warp = (tid >> 5) & 3;
        uint32_t ph = 0;
        const uint32_t relbar = lane < 2 ? mapa(bars + 8, lane) : 0;
        float acc[128];
        gemm_mainloop(acc, sb, bars, wg, relbar, ph, true);
        asm volatile("bar.sync %0, 128;" ::"r"(1 + wg) : "memory");
        const int row = warp * 16 + (lane & 7) + ((lane >> 3) & 1) * 8;
#pragma unroll
        for (int ch = 0; ch < 4; ch++) {
            const uint32_t base = sb + ch * G_STAGE + wg * 8192 + row * 128;
#pragma unroll
            for (int jj = 0; jj < 4; jj++) {
                const float* v = &acc[32 * ch + 8 * jj];
                uint32_t addr = base + (((2 * jj + (lane >> 4)) ^ (lane & 7)) << 4);
                asm volatile("stmatrix.sync.aligned.m8n8.x4.shared.b16 [%0], {%1, %2, %3, %4};" ::"r"(addr), "r"(pack_bf16(v[0], v[1])), "r"(pack_bf16(v[2], v[3])),
                             "r"(pack_bf16(v[4], v[5])), "r"(pack_bf16(v[6], v[7])) : "memory");
            }
            asm volatile("fence.proxy.async.shared::cta;" ::: "memory");
            asm volatile("bar.sync %0, 128;" ::"r"(1 + wg) : "memory");
            if ((tid & 127) == 0) {
                tma_st(&mOut, sb + ch * G_STAGE + wg * 8192, br * 1024 + nb * 256 + ch * 64, mblk * 128 + wg * 64);
                asm volatile("cp.async.bulk.commit_group;" ::: "memory");
            }
        }
        if ((tid & 127) == 0) asm volatile("cp.async.bulk.wait_group 0;" ::: "memory");
    }
}

constexpr int A_KVS = 512;
constexpr int A_ST = 3;
constexpr int A_STAGE = A_KVS * 128;
constexpr int A_SMEM = A_ST * A_STAGE + 1024 + 1024 + 128;
constexpr int A_NSTEP = SEQ / A_KVS;
constexpr int PNUM = 8, PDEN = 16;

__device__ __forceinline__ uint32_t hfma2(uint32_t a, uint32_t b, uint32_t c) { uint32_t d; asm("fma.rn.f16x2 %0, %1, %2, %3;" : "=r"(d) : "r"(a), "r"(b), "r"(c)); return d; }
__device__ __forceinline__ uint32_t ex2_pair_sw(float a, float b) {
    float ta = a + 24641.0f, tb = b + 24641.0f;
    uint32_t A = __byte_perm(__float_as_uint(ta), __float_as_uint(tb), 0x5410);
    uint32_t w; asm("lop3.b32 %0, %1, 0x01FF01FF, %2, 0xEA;" : "=r"(w) : "r"(A), "r"(0x3C003C00u));
    uint32_t h = hfma2(w, 0x0ce20ce2u, 0x8f568f56u);
    h = hfma2(h, w, 0x11921192u);
    h = hfma2(h, w, 0x1e751e75u);
    uint32_t e; asm("and.b32 %0, %1, 0xFE00FE00;" : "=r"(e) : "r"(A));
    return (e >> 2) + h;
}

template <bool FAST>
__device__ __forceinline__ void attn_consumer(uint32_t sb, uint32_t ones, uint32_t bars, int wg, int tid) {
    constexpr int BN = 64, IPS = A_KVS / BN;
    const int lane = tid & 31, warp = (tid >> 5) & 3, g = lane >> 2, c = lane & 3;
    float S[BN / 2], Oa[20];
    uint32_t P[BN / 4], Qf[8], Qn[8];
    float m0 = -INFINITY, m1 = -INFINITY;
    const uint32_t KHI = (512 >> 4) | (2u << 30);
    const uint32_t kd0 = (sb >> 4) | (1 << 16);
    const uint32_t vd0 = ((sb + A_KVS * 64) >> 4) | (((ones - (sb + A_KVS * 64)) >> 4) << 16);
    constexpr int VINC = 1 - 65536;
    auto mk = [&](uint32_t lo) { return ((uint64_t)KHI << 32) | lo; };
    auto qk = [&](uint64_t d) {
        wgmma_rs_n64_t0(S, Qf[0], Qf[1], Qf[2], Qf[3], d, 0);
        wgmma_rs_n64_t0(S, Qf[4], Qf[5], Qf[6], Qf[7], d + 2, 1);
    };
    const int row0 = (blockIdx.x & 7) * 256 + wg * 64 + warp * 16 + g;
    auto loadq = [&](uint32_t (&q)[8], int bh) {
        const uint32_t* qp = (const uint32_t*)(g_Q + ((size_t)bh * SEQ + row0) * 4);
#pragma unroll
        for (int k = 0; k < 2; k++) {
            q[4 * k + 0] = __ldcg(qp + (2 * k) * 4 + c);
            q[4 * k + 1] = __ldcg(qp + 8 * 16 + (2 * k) * 4 + c);
            q[4 * k + 2] = __ldcg(qp + (2 * k + 1) * 4 + c);
            q[4 * k + 3] = __ldcg(qp + 8 * 16 + (2 * k + 1) * 4 + c);
        }
    };
    uint32_t stx = 0, ph = 0, relbar = 0;
    loadq(Qf, blockIdx.x >> 3);
#pragma unroll
    for (int i = 0; i < 20; i++) Oa[i] = 0.f;
    pin(Qf); pin(Oa);
    mbar_wait(bars, 0);
    wg_fence();
    qk(mk(kd0));
    wg_commit();
#pragma unroll 1
    for (int r = 0; r < 4; r++) {
        const int bh = r * 16 + (blockIdx.x >> 3);
        loadq(Qn, r < 3 ? bh + 16 : bh);
#pragma unroll 1
        for (int j = 0; j < A_NSTEP; j++) {
            const uint64_t kd = mk(kd0 + stx * (A_STAGE / 256));
            const uint64_t vd = mk(vd0 + stx * (uint32_t)((A_STAGE / 256) * VINC));
            uint32_t nstx = stx + 16;
            if (nstx == A_ST * 16) { nstx = 0; ph ^= 1; }
            const uint64_t nkd = mk(kd0 + nstx * (A_STAGE / 256));
#pragma unroll(FAST ? IPS : 1)
            for (int i = 0; i < IPS; i++) {
                wg_wait<0>();
                pin(S);
                if (i == 0) { if (relbar) mbar_arrive(relbar); relbar = (lane == 0) ? bars + stx + 8 : 0; }
                if constexpr (FAST) {
#pragma unroll
                    for (int e = 0; e < BN / 4; e++)
                        P[e] = (((e * PNUM) % PDEN) < PNUM) ? ex2_pair_sw(S[2 * e], S[2 * e + 1]) : pack_bf16(ex2f(S[2 * e]), ex2f(S[2 * e + 1]));
                } else {
                    pin(Oa);
                    float n0 = m0, n1 = m1;
#pragma unroll
                    for (int e = 0; e < BN / 8; e++) { n0 = fmaxf(n0, fmaxf(S[4 * e], S[4 * e + 1])); n1 = fmaxf(n1, fmaxf(S[4 * e + 2], S[4 * e + 3])); }
                    n0 = fmaxf(n0, shx(n0, 1)); n1 = fmaxf(n1, shx(n1, 1));
                    n0 = fmaxf(n0, shx(n0, 2)); n1 = fmaxf(n1, shx(n1, 2));
                    const float b0 = (n0 == -INFINITY) ? 0.f : n0, b1 = (n1 == -INFINITY) ? 0.f : n1;
                    const float a0 = ex2f(m0 - b0), a1 = ex2f(m1 - b1);
                    m0 = n0; m1 = n1;
#pragma unroll
                    for (int e = 0; e < 5; e++) { Oa[4 * e] *= a0; Oa[4 * e + 1] *= a0; Oa[4 * e + 2] *= a1; Oa[4 * e + 3] *= a1; }
#pragma unroll
                    for (int e = 0; e < BN / 4; e++) { const float b = (e & 1) ? b1 : b0; P[e] = pack_bf16(ex2f(S[2 * e] - b), ex2f(S[2 * e + 1] - b)); }
                    pin(Oa);
                }
                pin(P);
                if (i == IPS - 1) {
                    if (j == A_NSTEP - 1) {
#pragma unroll
                        for (int k = 0; k < 8; k++) Qf[k] = Qn[k];
                    }
                    if (r < 3 || j < A_NSTEP - 1) mbar_wait(bars + nstx, ph);
                }
                pin(Qf);
                wg_fence();
                qk(i == IPS - 1 ? nkd : kd + (i + 1) * BN * 4);
#pragma unroll
                for (int k = 0; k < BN / 16; k++)
                    wgmma_rs_n40_t1(Oa, P[4 * k], P[4 * k + 1], P[4 * k + 2], P[4 * k + 3], vd + (long long)((i * BN * 4 + k * 64) * VINC), (k == 0) ? (i | j) : 1);
                wg_commit();
            }
            stx = nstx;
        }
        wg_wait<0>();
        pin(Oa);
        m0 = m1 = -INFINITY;
        const float l0 = __shfl_sync(0xffffffffu, Oa[16], lane & ~3);
        const float l1 = __shfl_sync(0xffffffffu, Oa[18], lane & ~3);
        const float r0 = __fdividef(1.0f, l0), r1 = __fdividef(1.0f, l1);
        uint4* op = g_O + ((size_t)(bh >> 5) * SEQ + row0) * 128 + (bh & 31) * 4 + c;
        op[0] = make_uint4(pack_bf16(Oa[0] * r0, Oa[1] * r0), pack_bf16(Oa[4] * r0, Oa[5] * r0), pack_bf16(Oa[8] * r0, Oa[9] * r0), pack_bf16(Oa[12] * r0, Oa[13] * r0));
        op[8 * 128] = make_uint4(pack_bf16(Oa[2] * r1, Oa[3] * r1), pack_bf16(Oa[6] * r1, Oa[7] * r1), pack_bf16(Oa[10] * r1, Oa[11] * r1), pack_bf16(Oa[14] * r1, Oa[15] * r1));
    }
    pin(S);
}

__global__ void __launch_bounds__(640, 1) attn_kernel() {
    extern __shared__ uint8_t smem_raw[];
    const uint32_t sb = (smem_u32(smem_raw) + 1023) & ~1023u;
    const uint32_t ones = sb + A_ST * A_STAGE;
    const uint32_t bars = ones + 1024;
    const int tid = threadIdx.x, wg = tid >> 7;
    if (tid < 64) asm volatile("st.shared.v4.u32 [%0], {%1, %2, %2, %2};" ::"r"(ones + tid * 16), "r"(0x3F80u), "r"(0u) : "memory");
    if (tid == 512) {
        for (int s = 0; s < A_ST; s++) { mbar_init(bars + 16 * s, 1); mbar_init(bars + 16 * s + 8, 16); }
        asm volatile("fence.mbarrier_init.release.cluster;" ::: "memory");
    }
    asm volatile("fence.proxy.async.shared::cta;" ::: "memory");
    __syncthreads();
    pdl_launch();
    pdl_wait();
    if (wg == 4) {
        reg_dec<24>();
        if (tid == 512) {
            int st = 0, ph = 1;
            for (int r = 0; r < 4; r++) {
                const int kvh = r < 2 ? 0 : (r - 2) * 16 + (blockIdx.x >> 3) + 1;
                const uint4* kp = g_K + (size_t)kvh * SEQ * 4;
                const uint4* vp = g_V + (size_t)kvh * SEQ * 4;
                for (int j = 0; j < A_NSTEP; j++) {
                    mbar_wait(bars + 16 * st + 8, ph);
                    mbar_expect_tx(bars + 16 * st, A_STAGE);
                    bulk_g2s(sb + st * A_STAGE, kp + j * A_KVS * 4, A_KVS * 64, bars + 16 * st);
                    bulk_g2s(sb + st * A_STAGE + A_KVS * 64, vp + j * A_KVS * 4, A_KVS * 64, bars + 16 * st);
                    if (++st == A_ST) { st = 0; ph ^= 1; }
                }
            }
        }
    } else {
        reg_inc<112>();
        const int lane = tid & 31;
        bool safe = true;
#pragma unroll
        for (int r = 0; r < 4; r++) {
            const int bh = r * 16 + (blockIdx.x >> 3), kvh = r < 2 ? 0 : bh - 31;
            const uint4 q = __ldcg((const uint4*)(g_nrm + bh * 128 + (blockIdx.x & 7) * 16 + wg * 4));
            const uint4 k = __ldcg((const uint4*)(g_nrm + (64 + kvh) * 128) + lane);
            const uint4 v = __ldcg((const uint4*)(g_nrm + (97 + kvh) * 128) + lane);
            const float qm = __uint_as_float(max(max(q.x, q.y), max(q.z, q.w)));
            const float km = __uint_as_float(__reduce_max_sync(0xffffffffu, max(max(k.x, k.y), max(k.z, k.w))));
            const float vm = __uint_as_float(__reduce_max_sync(0xffffffffu, max(max(v.x, v.y), max(v.z, v.w))));
            safe = safe && (qm * km <= 3600.0f) && (vm <= 1.0e24f) && (vm >= 1.0e-24f);
        }
        if (__all_sync(0xffffffffu, safe)) attn_consumer<true>(sb, ones, bars, wg, tid);
        else attn_consumer<false>(sb, ones, bars, wg, tid);
    }
}

typedef CUresult (*EncodeFn)(CUtensorMap*, CUtensorMapDataType, cuuint32_t, void*, const cuuint64_t*, const cuuint64_t*, const cuuint32_t*,
                             const cuuint32_t*, CUtensorMapInterleave, CUtensorMapSwizzle, CUtensorMapL2promotion, CUtensorMapFloatOOBfill);

static void make_map(EncodeFn enc, CUtensorMap* m, const void* p, int cols, int rows, int bx, int by, CUtensorMapSwizzle sw) {
    cuuint64_t dims[2] = {(cuuint64_t)cols, (cuuint64_t)rows};
    cuuint64_t strides[1] = {(cuuint64_t)cols * 2};
    cuuint32_t box[2] = {(cuuint32_t)bx, (cuuint32_t)by};
    cuuint32_t es[2] = {1, 1};
    enc(m, CU_TENSOR_MAP_DATA_TYPE_BFLOAT16, 2, (void*)p, dims, strides, box, es, CU_TENSOR_MAP_INTERLEAVE_NONE, sw,
        CU_TENSOR_MAP_L2_PROMOTION_L2_256B, CU_TENSOR_MAP_FLOAT_OOB_FILL_NONE);
}

extern "C" void kernel_launch(void* const* d_in, const int* in_sizes, int n_in, void* d_out, int out_size) {
    (void)in_sizes; (void)n_in; (void)out_size;
    void* fn = nullptr;
    cudaDriverEntryPointQueryResult qr;
    cudaGetDriverEntryPoint("cuTensorMapEncodeTiled", &fn, cudaEnableDefault, &qr);
    EncodeFn enc = (EncodeFn)fn;
    void* pO = nullptr;
    cudaGetSymbolAddress(&pO, g_O);
    CUtensorMap mXA, mXB, mWq, mWqkv, mWk, mWv, mO, mWoA, mWoB, mOut;
    make_map(enc, &mXA, d_in[0], 1024, 2048, 64, 128, CU_TENSOR_MAP_SWIZZLE_128B);
    make_map(enc, &mWq, d_in[1], 1024, 1024, 64, 64, CU_TENSOR_MAP_SWIZZLE_128B);
    make_map(enc, &mWk, d_in[2], 32, 1024, 32, 64, CU_TENSOR_MAP_SWIZZLE_64B);
    make_map(enc, &mWv, d_in[3], 32, 1024, 32, 64, CU_TENSOR_MAP_SWIZZLE_64B);
    make_map(enc, &mWoA, d_in[4], 1024, 1024, 64, 64, CU_TENSOR_MAP_SWIZZLE_128B);
    make_map(enc, &mXB, d_in[5], 1024, 2048, 64, 128, CU_TENSOR_MAP_SWIZZLE_128B);
    make_map(enc, &mWqkv, d_in[6], 3072, 1024, 64, 64, CU_TENSOR_MAP_SWIZZLE_128B);
    make_map(enc, &mWoB, d_in[7], 1024, 1024, 64, 64, CU_TENSOR_MAP_SWIZZLE_128B);
    make_map(enc, &mO, pO, 1024, 4096, 64, 128, CU_TENSOR_MAP_SWIZZLE_128B);
    make_map(enc, &mOut, d_out, 2048, 2048, 64, 64, CU_TENSOR_MAP_SWIZZLE_128B);
    cudaFuncSetAttribute(proj_kernel, cudaFuncAttributeMaxDynamicSharedMemorySize, G_SMEM);
    cudaFuncSetAttribute(outproj_kernel, cudaFuncAttributeMaxDynamicSharedMemorySize, G_SMEM);
    cudaFuncSetAttribute(attn_kernel, cudaFuncAttributeMaxDynamicSharedMemorySize, A_SMEM);

    cudaStream_t st = cudaStreamPerThread;
    cudaLaunchAttribute pdl[1];
    pdl[0].id = cudaLaunchAttributeProgrammaticStreamSerialization;
    pdl[0].val.programmaticStreamSerializationAllowed = 1;
    cudaLaunchConfig_t cfg = {};
    cfg.stream = st;
    cfg.gridDim = dim3(132); cfg.blockDim = dim3(384); cfg.dynamicSmemBytes = G_SMEM;
    cudaLaunchKernelEx(&cfg, proj_kernel, mXA, mXB, mWq, mWqkv, mWk, mWv);
    cfg.attrs = pdl; cfg.numAttrs = 1;
    cfg.gridDim = dim3(128); cfg.blockDim = dim3(640); cfg.dynamicSmemBytes = A_SMEM;
    cudaLaunchKernelEx(&cfg, attn_kernel);
    cfg.gridDim = dim3(128); cfg.blockDim = dim3(384); cfg.dynamicSmemBytes = G_SMEM;
    cudaLaunchKernelEx(&cfg, outproj_kernel, mO, mWoA, mWoB, mOut);
}
```

```cpp
#include <cuda_runtime.h>
#include <cuda_bf16.h>
#include <cuda.h>
#include <stdint.h>

constexpr int SEQ = 2048;

__device__ __align__(1024) uint4 g_Q[64 * SEQ * 4];
__device__ __align__(1024) uint4 g_K[33 * SEQ * 4];
__device__ __align__(1024) uint4 g_V[33 * SEQ * 4];
__device__ __align__(1024) uint4 g_O[2 * SEQ * 128];
__device__ __align__(16) float g_nrm[130 * 128];
__device__ unsigned g_cnt[34 * 32];
__device__ unsigned g_epoch[128];

#define TL(k, slot)

__device__ __forceinline__ void wgmma_rs_n40_t1(float (&d)[20], uint32_t a0, uint32_t a1, uint32_t a2, uint32_t a3, uint64_t descB, int scaleD) {
    asm volatile("{\n.reg .pred p;\nsetp.ne.b32 p, %25, 0;\n"
        "wgmma.mma_async.sync.aligned.m64n40k16.f32.bf16.bf16 "
        "{%0, %1, %2, %3, %4, %5, %6, %7, %8, %9, %10, %11, %12, %13, %14, %15, "
        "%16, %17, %18, %19}, "
        "{%20, %21, %22, %23}, %24, p, 1, 1, 1;\n}\n"
        : "+f"(d[0]), "+f"(d[1]), "+f"(d[2]), "+f"(d[3]), "+f"(d[4]), "+f"(d[5]), "+f"(d[6]), "+f"(d[7]),
          "+f"(d[8]), "+f"(d[9]), "+f"(d[10]), "+f"(d[11]), "+f"(d[12]), "+f"(d[13]), "+f"(d[14]), "+f"(d[15]),
          "+f"(d[16]), "+f"(d[17]), "+f"(d[18]), "+f"(d[19])
        : "r"(a0), "r"(a1), "r"(a2), "r"(a3), "l"(descB), "r"(scaleD));
}
__device__ __forceinline__ void wgmma_rs_n64_t0(float (&d)[32], uint32_t a0, uint32_t a1, uint32_t a2, uint32_t a3, uint64_t descB, int scaleD) {
    asm volatile("{\n.reg .pred p;\nsetp.ne.b32 p, %37, 0;\n"
        "wgmma.mma_async.sync.aligned.m64n64k16.f32.bf16.bf16 "
        "{%0, %1, %2, %3, %4, %5, %6, %7, %8, %9, %10, %11, %12, %13, %14, %15, "
        "%16, %17, %18, %19, %20, %21, %22, %23, %24, %25, %26, %27, %28, %29, %30, %31}, "
        "{%32, %33, %34, %35}, %36, p, 1, 1, 0;\n}\n"
        : "+f"(d[0]), "+f"(d[1]), "+f"(d[2]), "+f"(d[3]), "+f"(d[4]), "+f"(d[5]), "+f"(d[6]), "+f"(d[7]),
          "+f"(d[8]), "+f"(d[9]), "+f"(d[10]), "+f"(d[11]), "+f"(d[12]), "+f"(d[13]), "+f"(d[14]), "+f"(d[15]),
          "+f"(d[16]), "+f"(d[17]), "+f"(d[18]), "+f"(d[19]), "+f"(d[20]), "+f"(d[21]), "+f"(d[22]), "+f"(d[23]),
          "+f"(d[24]), "+f"(d[25]), "+f"(d[26]), "+f"(d[27]), "+f"(d[28]), "+f"(d[29]), "+f"(d[30]), "+f"(d[31])
        : "r"(a0), "r"(a1), "r"(a2), "r"(a3), "l"(descB), "r"(scaleD));
}
__device__ __forceinline__ void wgmma_ss_n128_t1(float (&d)[64], uint64_t descA, uint64_t descB, int scaleD) {
    asm volatile("{\n.reg .pred p;\nsetp.ne.b32 p, %66, 0;\n"
        "wgmma.mma_async.sync.aligned.m64n128k16.f32.bf16.bf16 "
        "{%0, %1, %2, %3, %4, %5, %6, %7, %8, %9, %10, %11, %12, %13, %14, %15, "
        "%16, %17, %18, %19, %20, %21, %22, %23, %24, %25, %26, %27, %28, %29, %30, %31, "
        "%32, %33, %34, %35, %36, %37, %38, %39, %40, %41, %42, %43, %44, %45, %46, %47, "
        "%48, %49, %50, %51, %52, %53, %54, %55, %56, %57, %58, %59, %60, %61, %62, %63}, "
        "%64, %65, p, 1, 1, 0, 1;\n}\n"
        : "+f"(d[0]), "+f"(d[1]), "+f"(d[2]), "+f"(d[3]), "+f"(d[4]), "+f"(d[5]), "+f"(d[6]), "+f"(d[7]),
          "+f"(d[8]), "+f"(d[9]), "+f"(d[10]), "+f"(d[11]), "+f"(d[12]), "+f"(d[13]), "+f"(d[14]), "+f"(d[15]),
          "+f"(d[16]), "+f"(d[17]), "+f"(d[18]), "+f"(d[19]), "+f"(d[20]), "+f"(d[21]), "+f"(d[22]), "+f"(d[23]),
          "+f"(d[24]), "+f"(d[25]), "+f"(d[26]), "+f"(d[27]), "+f"(d[28]), "+f"(d[29]), "+f"(d[30]), "+f"(d[31]),
          "+f"(d[32]), "+f"(d[33]), "+f"(d[34]), "+f"(d[35]), "+f"(d[36]), "+f"(d[37]), "+f"(d[38]), "+f"(d[39]),
          "+f"(d[40]), "+f"(d[41]), "+f"(d[42]), "+f"(d[43]), "+f"(d[44]), "+f"(d[45]), "+f"(d[46]), "+f"(d[47]),
          "+f"(d[48]), "+f"(d[49]), "+f"(d[50]), "+f"(d[51]), "+f"(d[52]), "+f"(d[53]), "+f"(d[54]), "+f"(d[55]),
          "+f"(d[56]), "+f"(d[57]), "+f"(d[58]), "+f"(d[59]), "+f"(d[60]), "+f"(d[61]), "+f"(d[62]), "+f"(d[63])
        : "l"(descA), "l"(descB), "r"(scaleD));
}
__device__ __forceinline__ void wgmma_ss_n64_t1(float (&d)[32], uint64_t descA, uint64_t descB, int scaleD) {
    asm volatile("{\n.reg .pred p;\nsetp.ne.b32 p, %34, 0;\n"
        "wgmma.mma_async.sync.aligned.m64n64k16.f32.bf16.bf16 "
        "{%0, %1, %2, %3, %4, %5, %6, %7, %8, %9, %10, %11, %12, %13, %14, %15, "
        "%16, %17, %18, %19, %20, %21, %22, %23, %24, %25, %26, %27, %28, %29, %30, %31}, "
        "%32, %33, p, 1, 1, 0, 1;\n}\n"
        : "+f"(d[0]), "+f"(d[1]), "+f"(d[2]), "+f"(d[3]), "+f"(d[4]), "+f"(d[5]), "+f"(d[6]), "+f"(d[7]),
          "+f"(d[8]), "+f"(d[9]), "+f"(d[10]), "+f"(d[11]), "+f"(d[12]), "+f"(d[13]), "+f"(d[14]), "+f"(d[15]),
          "+f"(d[16]), "+f"(d[17]), "+f"(d[18]), "+f"(d[19]), "+f"(d[20]), "+f"(d[21]), "+f"(d[22]), "+f"(d[23]),
          "+f"(d[24]), "+f"(d[25]), "+f"(d[26]), "+f"(d[27]), "+f"(d[28]), "+f"(d[29]), "+f"(d[30]), "+f"(d[31])
        : "l"(descA), "l"(descB), "r"(scaleD));
}

__device__ __forceinline__ void wg_fence() { asm volatile("wgmma.fence.sync.aligned;" ::: "memory"); }
__device__ __forceinline__ void wg_commit() { asm volatile("wgmma.commit_group.sync.aligned;" ::: "memory"); }
template <int N> __device__ __forceinline__ void wg_wait() { asm volatile("wgmma.wait_group.sync.aligned %0;" ::"n"(N) : "memory"); }
template <int N> __device__ __forceinline__ void pin(float (&r)[N]) {
#pragma unroll
    for (int i = 0; i < N; i++) asm volatile("" : "+f"(r[i])::"memory");
}
template <int N> __device__ __forceinline__ void pin(uint32_t (&r)[N]) {
#pragma unroll
    for (int i = 0; i < N; i++) asm volatile("" : "+r"(r[i])::"memory");
}
__device__ __forceinline__ uint64_t mkdesc(uint32_t addr, uint32_t lbo, uint32_t sbo, int swz) {
    return (uint64_t)((addr & 0x3FFFF) >> 4) | ((uint64_t)((lbo >> 4) & 0x3FFF) << 16) | ((uint64_t)((sbo >> 4) & 0x3FFF) << 32) | ((uint64_t)swz << 62);
}
__device__ __forceinline__ uint32_t smem_u32(const void* p) { return (uint32_t)__cvta_generic_to_shared(p); }
__device__ __forceinline__ void mbar_init(uint32_t bar, uint32_t cnt) { asm volatile("mbarrier.init.shared::cta.b64 [%0], %1;" ::"r"(bar), "r"(cnt) : "memory"); }
__device__ __forceinline__ void mbar_arrive(uint32_t bar) { asm volatile("mbarrier.arrive.shared::cta.b64 _, [%0];" ::"r"(bar) : "memory"); }
__device__ __forceinline__ void mbar_arrive_cluster(uint32_t bar) { asm volatile("mbarrier.arrive.shared::cluster.b64 _, [%0];" ::"r"(bar) : "memory"); }
__device__ __forceinline__ void mbar_expect_tx(uint32_t bar, uint32_t bytes) { asm volatile("mbarrier.arrive.expect_tx.shared::cta.b64 _, [%0], %1;" ::"r"(bar), "r"(bytes) : "memory"); }
__device__ __forceinline__ void mbar_wait(uint32_t bar, uint32_t parity) {
    asm volatile("{\n.reg .pred p;\n.reg .u32 cnt;\nmov.u32 cnt, 0;\nLAB_WAIT:\n"
                 "mbarrier.try_wait.parity.shared::cta.b64 p, [%0], %1;\n"
                 "@p bra LAB_DONE;\n"
                 "add.u32 cnt, cnt, 1;\n"
                 "setp.lt.u32 p, cnt, 0x1000000;\n"
                 "@p bra LAB_WAIT;\n"
                 "trap;\n"
                 "LAB_DONE:\n}\n" ::"r"(bar), "r"(parity) : "memory");
}
__device__ __forceinline__ uint32_t mapa(uint32_t addr, uint32_t rank) { uint32_t r; asm("mapa.shared::cluster.u32 %0, %1, %2;" : "=r"(r) : "r"(addr), "r"(rank)); return r; }
__device__ __forceinline__ void bulk_g2s(uint32_t dst, const void* src, uint32_t bytes, uint32_t bar) {
    asm volatile("cp.async.bulk.shared::cluster.global.mbarrier::complete_tx::bytes [%0], [%1], %2, [%3];" ::"r"(dst), "l"(src), "r"(bytes), "r"(bar) : "memory");
}
__device__ __forceinline__ void tma_ld(uint32_t dst, const CUtensorMap* m, int x, int y, uint32_t bar) {
    asm volatile("cp.async.bulk.tensor.2d.shared::cluster.global.mbarrier::complete_tx::bytes [%0], [%1, {%3, %4}], [%2];" ::"r"(dst), "l"(m), "r"(bar), "r"(x), "r"(y) : "memory");
}
__device__ __forceinline__ void tma_ld_mc(uint32_t dst, const CUtensorMap* m, int x, int y, uint32_t bar, uint16_t mask) {
    asm volatile("cp.async.bulk.tensor.2d.shared::cluster.global.mbarrier::complete_tx::bytes.multicast::cluster [%0], [%1, {%3, %4}], [%2], %5;" ::"r"(dst), "l"(m), "r"(bar), "r"(x), "r"(y), "h"(mask) : "memory");
}
__device__ __forceinline__ void tma_st(const CUtensorMap* m, uint32_t src, int x, int y) {
    asm volatile("cp.async.bulk.tensor.2d.global.shared::cta.bulk_group [%0, {%2, %3}], [%1];" ::"l"(m), "r"(src), "r"(x), "r"(y) : "memory");
}
__device__ __forceinline__ void prefetch_tmap(const CUtensorMap* m) { asm volatile("prefetch.tensormap [%0];" ::"l"(m) : "memory"); }
__device__ __forceinline__ void bulk_g2s_mc(uint32_t dst, const void* src, uint32_t bytes, uint32_t bar, uint16_t mask) {
    asm volatile("cp.async.bulk.shared::cluster.global.mbarrier::complete_tx::bytes.multicast::cluster [%0], [%1], %2, [%3], %4;" ::"r"(dst), "l"(src), "r"(bytes), "r"(bar), "h"(mask) : "memory");
}
__device__ __forceinline__ void bulk_s2g(void* dst, uint32_t src, uint32_t bytes) {
    asm volatile("cp.async.bulk.global.shared::cta.bulk_group [%0], [%1], %2;" ::"l"(dst), "r"(src), "r"(bytes) : "memory");
}
__device__ __forceinline__ void fence_async() { asm volatile("fence.proxy.async;" ::: "memory"); }
__device__ __forceinline__ void fence_async_smem() { asm volatile("fence.proxy.async.shared::cta;" ::: "memory"); }
__device__ __forceinline__ void cnt_signal(int idx) { asm volatile("fence.acq_rel.gpu;\nred.relaxed.gpu.global.add.u32 [%0], 1;" ::"l"(g_cnt + idx * 32) : "memory"); }
__device__ __forceinline__ void cnt_wait(int idx, uint32_t target) {
    for (int it = 0;; it++) {
        uint32_t v;
        asm volatile("ld.acquire.gpu.global.u32 %0, [%1];" : "=r"(v) : "l"(g_cnt + idx * 32) : "memory");
        if ((int)(v - target) >= 0) break;
        if (it > (1 << 22)) __trap();
        __nanosleep(64);
    }
}
__device__ __forceinline__ uint32_t lds32(uint32_t a) { uint32_t v; asm volatile("ld.shared.u32 %0, [%1];" : "=r"(v) : "r"(a) : "memory"); return v; }
__device__ __forceinline__ void sts32(uint32_t a, uint32_t v) { asm volatile("st.shared.u32 [%0], %1;" ::"r"(a), "r"(v) : "memory"); }
__device__ __forceinline__ void sts128(uint32_t a, uint4 v) { asm volatile("st.shared.v4.u32 [%0], {%1, %2, %3, %4};" ::"r"(a), "r"(v.x), "r"(v.y), "r"(v.z), "r"(v.w) : "memory"); }
__device__ __forceinline__ uint4 lds128(uint32_t a) { uint4 v; asm volatile("ld.shared.v4.u32 {%0, %1, %2, %3}, [%4];" : "=r"(v.x), "=r"(v.y), "=r"(v.z), "=r"(v.w) : "r"(a) : "memory"); return v; }
__device__ __forceinline__ float shx(float v, int m) { return __shfl_xor_sync(0xffffffffu, v, m); }
__device__ __forceinline__ float ex2f(float x) { float y; asm("ex2.approx.ftz.f32 %0, %1;" : "=f"(y) : "f"(x)); return y; }
__device__ __forceinline__ uint32_t pack_bf16(float lo, float hi) { uint32_t r; asm("cvt.rn.bf16x2.f32 %0, %1, %2;" : "=r"(r) : "f"(hi), "f"(lo)); return r; }
template <int R> __device__ __forceinline__ void reg_inc() { asm volatile("setmaxnreg.inc.sync.aligned.u32 %0;" ::"n"(R)); }
template <int R> __device__ __forceinline__ void reg_dec() { asm volatile("setmaxnreg.dec.sync.aligned.u32 %0;" ::"n"(R)); }

constexpr int SLOT = 49152;
constexpr int OFF_Q = 4 * SLOT;
constexpr int OFF_ONES = OFF_Q + 32768;
constexpr int OFF_BAR = OFF_ONES + 1024;
constexpr int SMEM_BYTES = OFF_BAR + 128 + 1024;
constexpr int B_SIG = 64, B_DEP = 72, B_FLAG = 88, B_EPOCH = 96;

__device__ __forceinline__ void gemm_kstep(float (&acc)[64], uint32_t sb, uint64_t da0, uint64_t db0, uint32_t relbar, int kb, bool rel) {
    const int s = kb & 3;
    mbar_wait(sb + OFF_BAR + 16 * s, (kb >> 2) & 1);
    const uint64_t da = da0 + s * (SLOT / 16), db = db0 + s * (SLOT / 16);
    wg_fence();
#pragma unroll
    for (int k = 0; k < 4; k++) wgmma_ss_n128_t1(acc, da + 2 * k, db + 128 * k, (k > 0) ? 1 : kb);
    wg_commit();
    wg_wait<1>();
    if (rel && relbar) mbar_arrive_cluster(relbar + 16 * ((kb - 1) & 3));
}

__device__ __forceinline__ void proj_pack(const float (&acc)[64], uint4 (&pk)[8], float sc, float* nrm, int lane) {
    const int c = lane & 3, g = lane >> 2;
    float ss[8];
#pragma unroll
    for (int h = 0; h < 4; h++) {
        float v[16];
#pragma unroll
        for (int i = 0; i < 16; i++) v[i] = acc[16 * h + i] * sc;
        pk[2 * h] = make_uint4(pack_bf16(v[0], v[1]), pack_bf16(v[4], v[5]), pack_bf16(v[8], v[9]), pack_bf16(v[12], v[13]));
        pk[2 * h + 1] = make_uint4(pack_bf16(v[2], v[3]), pack_bf16(v[6], v[7]), pack_bf16(v[10], v[11]), pack_bf16(v[14], v[15]));
        float a = 0.f, b = 0.f;
#pragma unroll
        for (int j = 0; j < 4; j++) {
            a = fmaf(v[4 * j], v[4 * j], fmaf(v[4 * j + 1], v[4 * j + 1], a));
            b = fmaf(v[4 * j + 2], v[4 * j + 2], fmaf(v[4 * j + 3], v[4 * j + 3], b));
        }
        ss[h] = a; ss[4 + h] = b;
    }
    float t4[4], t2[2];
#pragma unroll
    for (int h = 0; h < 4; h++) t4[h] = ((c & 1) ? ss[4 + h] : ss[h]) + shx((c & 1) ? ss[h] : ss[4 + h], 1);
#pragma unroll
    for (int h = 0; h < 2; h++) t2[h] = ((c & 2) ? t4[2 + h] : t4[h]) + shx((c & 2) ? t4[h] : t4[2 + h], 2);
    uint32_t u = max(__float_as_uint((c & 1) ? t2[1] : t2[0]), __float_as_uint(shx((c & 1) ? t2[0] : t2[1], 1)));
    u = max(u, __shfl_xor_sync(0xffffffffu, u, 4));
    u = max(u, __shfl_xor_sync(0xffffffffu, u, 8));
    u = max(u, __shfl_xor_sync(0xffffffffu, u, 16));
    if (g == 0) nrm[c * 128] = __uint_as_float(u);
}

constexpr int PNUM = 8, PDEN = 16;

__device__ __forceinline__ uint32_t hfma2(uint32_t a, uint32_t b, uint32_t c) { uint32_t d; asm("fma.rn.f16x2 %0, %1, %2, %3;" : "=r"(d) : "r"(a), "r"(b), "r"(c)); return d; }
__device__ __forceinline__ uint32_t ex2_pair_sw(float a, float b) {
    float ta = a + 24641.0f, tb = b + 24641.0f;
    uint32_t A = __byte_perm(__float_as_uint(ta), __float_as_uint(tb), 0x5410);
    uint32_t w; asm("lop3.b32 %0, %1, 0x01FF01FF, %2, 0xEA;" : "=r"(w) : "r"(A), "r"(0x3C003C00u));
    uint32_t h = hfma2(w, 0x0ce20ce2u, 0x8f568f56u);
    h = hfma2(h, w, 0x11921192u);
    h = hfma2(h, w, 0x1e751e75u);
    uint32_t e; asm("and.b32 %0, %1, 0xFE00FE00;" : "=r"(e) : "r"(A));
    return (e >> 2) + h;
}

constexpr uint32_t KV_HI = (512 >> 4) | (2u << 30);
constexpr int VINC = 1 - 65536;
__device__ __forceinline__ uint64_t kvdesc(uint32_t lo) { return ((uint64_t)KV_HI << 32) | lo; }
__device__ __forceinline__ void attn_qk(float (&S)[32], const uint32_t (&Qf)[8], uint64_t d) {
    wgmma_rs_n64_t0(S, Qf[0], Qf[1], Qf[2], Qf[3], d, 0);
    wgmma_rs_n64_t0(S, Qf[4], Qf[5], Qf[6], Qf[7], d + 2, 1);
}
__device__ __forceinline__ void attn_loadq(uint32_t (&Qf)[8], uint32_t qa) {
#pragma unroll
    for (int j = 0; j < 4; j++) {
        Qf[(j >> 1) * 4 + (j & 1) * 2] = lds32(qa ^ (j << 4));
        Qf[(j >> 1) * 4 + (j & 1) * 2 + 1] = lds32((qa ^ (j << 4)) + 512);
    }
}

template <bool FAST>
__device__ __forceinline__ int attn_rounds(uint32_t sb, uint32_t qa, uint32_t relbar, uint4* op, int j, int lane) {
    float S[32], Oa[20];
    uint32_t P[16], Qf[8];
    float m0 = -INFINITY, m1 = -INFINITY;
    const uint32_t kd0 = (((sb & 0x3FFFF) + 16384) >> 4) | (1 << 16);
    const uint32_t vd0 = (((sb & 0x3FFFF) + 32768) >> 4) | (((OFF_ONES - 32768) >> 4) << 16);
#pragma unroll
    for (int i = 0; i < 20; i++) Oa[i] = 0.f;
    mbar_wait(sb + OFF_BAR, 0);
    attn_loadq(Qf, qa);
    pin(Oa); pin(Qf);
    wg_fence();
    attn_qk(S, Qf, kvdesc(kd0));
    wg_commit();
    if (threadIdx.x == 0) TL(0, 5);
    int jend = 32;
#pragma unroll 1
    do {
        const uint32_t s = j & 3, ns = (j + 1) & 3;
        const uint64_t kd = kvdesc(kd0 + s * (SLOT / 16));
        const uint64_t vd = kvdesc(vd0 + s * (uint32_t)((SLOT / 16) * VINC));
        const uint64_t nkd = kvdesc(kd0 + ns * (SLOT / 16));
#pragma unroll(FAST ? 4 : 1)
        for (int i = 0; i < 4; i++) {
            wg_wait<0>();
            pin(S);
            if (i == 0 && (j & 7) && relbar) mbar_arrive_cluster(relbar + 16 * ((j - 1) & 3));
            if constexpr (FAST) {
#pragma unroll
                for (int e = 0; e < 16; e++)
                    P[e] = (((e * PNUM) % PDEN) < PNUM) ? ex2_pair_sw(S[2 * e], S[2 * e + 1]) : pack_bf16(ex2f(S[2 * e]), ex2f(S[2 * e + 1]));
            } else {
                pin(Oa);
                float n0 = m0, n1 = m1;
#pragma unroll
                for (int e = 0; e < 8; e++) { n0 = fmaxf(n0, fmaxf(S[4 * e], S[4 * e + 1])); n1 = fmaxf(n1, fmaxf(S[4 * e + 2], S[4 * e + 3])); }
                n0 = fmaxf(n0, shx(n0, 1)); n1 = fmaxf(n1, shx(n1, 1));
                n0 = fmaxf(n0, shx(n0, 2)); n1 = fmaxf(n1, shx(n1, 2));
                const float b0 = (n0 == -INFINITY) ? 0.f : n0, b1 = (n1 == -INFINITY) ? 0.f : n1;
                const float a0 = ex2f(m0 - b0), a1 = ex2f(m1 - b1);
                m0 = n0; m1 = n1;
#pragma unroll
                for (int e = 0; e < 5; e++) { Oa[4 * e] *= a0; Oa[4 * e + 1] *= a0; Oa[4 * e + 2] *= a1; Oa[4 * e + 3] *= a1; }
#pragma unroll
                for (int e = 0; e < 16; e++) { const float b = (e & 1) ? b1 : b0; P[e] = pack_bf16(ex2f(S[2 * e] - b), ex2f(S[2 * e + 1] - b)); }
                pin(Oa);
            }
            pin(P);
            if (i == 3 && j != 31) {
                mbar_wait(sb + OFF_BAR + 16 * ns, ((j + 1) >> 2) & 1);
                if ((j & 7) == 7) attn_loadq(Qf, qa);
            }
            pin(Qf);
            wg_fence();
            attn_qk(S, Qf, i == 3 ? nkd : kd + (i + 1) * 256);
#pragma unroll
            for (int k = 0; k < 4; k++)
                wgmma_rs_n40_t1(Oa, P[4 * k], P[4 * k + 1], P[4 * k + 2], P[4 * k + 3], vd + (long long)((i * 256 + k * 64) * VINC), 1);
            wg_commit();
        }
        if ((j & 7) == 7) {
            wg_wait<0>();
            pin(Oa);
            if (relbar) mbar_arrive_cluster(relbar + 48);
            const float l0 = __shfl_sync(0xffffffffu, Oa[16], lane & ~3);
            const float l1 = __shfl_sync(0xffffffffu, Oa[18], lane & ~3);
            const float r0 = __fdividef(1.0f, l0), r1 = __fdividef(1.0f, l1);
            uint4* o = op + (j >> 4) * (SEQ * 128) + ((j >> 3) & 1) * 64;
            o[0] = make_uint4(pack_bf16(Oa[0] * r0, Oa[1] * r0), pack_bf16(Oa[4] * r0, Oa[5] * r0), pack_bf16(Oa[8] * r0, Oa[9] * r0), pack_bf16(Oa[12] * r0, Oa[13] * r0));
            o[8 * 128] = make_uint4(pack_bf16(Oa[2] * r1, Oa[3] * r1), pack_bf16(Oa[6] * r1, Oa[7] * r1), pack_bf16(Oa[10] * r1, Oa[11] * r1), pack_bf16(Oa[14] * r1, Oa[15] * r1));
            __syncwarp();
            if (lane == 0) mbar_arrive(sb + OFF_BAR + B_SIG);
            if (threadIdx.x == 0) TL(0, 6 + (j >> 3));
            if (FAST && j == 15) {
                mbar_wait(sb + OFF_BAR + B_DEP + 8, 0);
                if (!__all_sync(0xffffffffu, lds32(sb + OFF_BAR + B_FLAG + 4))) jend = 16;
            }
            m0 = m1 = -INFINITY;
#pragma unroll
            for (int i = 0; i < 20; i++) Oa[i] = 0.f;
            pin(Oa);
        }
    } while (++j < jend);
    wg_wait<0>();
    pin(S);
    return j;
}

struct Maps { CUtensorMap XA, XB, Wq, Wqkv, Wk, Wv, O, WoA, WoB, Out; };

__global__ void __cluster_dims__(2, 1, 1) __launch_bounds__(640, 1) mega_kernel(const __grid_constant__ Maps mp) {
    extern __shared__ uint8_t smem_raw[];
    const uint32_t sb = (smem_u32(smem_raw) + 1023) & ~1023u;
    const uint32_t bars = sb + OFF_BAR;
    const int tid = threadIdx.x, lane = tid & 31;
    const int wid = __shfl_sync(0xffffffffu, tid >> 5, 0), wg = wid >> 2;
    const int cid = blockIdx.x >> 1, rank = blockIdx.x & 1;
    const bool small = cid >= 64;
    const int mblk = 2 * (cid & 7) + rank, nb = (cid >> 3) & 3;
    const int hd = cid >> 2, rb = 2 * (cid & 3) + rank;
    if (tid == 0) TL(0, 0);
    if (tid == 512) {
        prefetch_tmap(cid < 32 || small ? &mp.XA : &mp.XB);
        prefetch_tmap(small ? &mp.Wk : (cid < 32 ? &mp.Wq : &mp.Wqkv));
        for (int s = 0; s < 4; s++) { mbar_init(bars + 16 * s, 1); mbar_init(bars + 16 * s + 8, small ? 16 : 32); }
        mbar_init(bars + B_SIG, 16); mbar_init(bars + B_DEP, 1); mbar_init(bars + B_DEP + 8, 1);
        asm volatile("fence.mbarrier_init.release.cluster;" ::: "memory");
    }
    if (tid < 64) { sts128(sb + OFF_ONES + tid * 16, make_uint4(0x3F80u, 0, 0, 0)); fence_async_smem(); }
    __syncthreads();
    asm volatile("barrier.cluster.arrive.relaxed.aligned;\nbarrier.cluster.wait.aligned;" ::: "memory");

    if (wg == 4) {
        reg_dec<32>();
        if (wid == 16) {
            if (lane == 0) {
                if (small) {
                    const int r0 = (blockIdx.x - 128) * 512;
                    for (int n = 0; n < 32; n++) {
                        const uint32_t fb = bars + 16 * (n & 3), st = sb + (n & 3) * SLOT;
                        const int k0 = (n & 15) * 64, r = r0 + (n >> 4) * 256;
                        mbar_wait(fb + 8, ((n >> 2) & 1) ^ 1);
                        mbar_expect_tx(fb, 40960);
                        tma_ld(st, &mp.XA, k0, r, fb);
                        tma_ld(st + 16384, &mp.XA, k0, r + 128, fb);
                        tma_ld(st + 32768, &mp.Wk, 0, k0, fb);
                        tma_ld(st + 36864, &mp.Wv, 0, k0, fb);
                    }
                } else {
                    for (int n = 0; n < 32; n++) {
                        const uint32_t fb = bars + 16 * (n & 3), st = sb + (n & 3) * SLOT;
                        const bool isA = (n < 16 && cid < 32);
                        const int k0 = (n & 15) * 64, n0 = (cid < 32 ? nb : (n < 16 ? 4 + nb : 8 + nb)) * 256 + rank * 128;
                        mbar_wait(fb + 8, ((n >> 2) & 1) ^ 1);
                        mbar_expect_tx(fb, SLOT);
                        tma_ld(st, isA ? &mp.XA : &mp.XB, k0, mblk * 128, fb);
                        tma_ld_mc(st + 16384 + rank * 16384, isA ? &mp.Wq : &mp.Wqkv, n0, k0, fb, 3);
                        tma_ld_mc(st + 24576 + rank * 16384, isA ? &mp.Wq : &mp.Wqkv, n0 + 64, k0, fb, 3);
                    }
                    for (int n = 0; n < 32; n++) {
                        const uint32_t fb = bars + 16 * (n & 3), st = sb + (n & 3) * SLOT;
                        const int r = n >> 3, j = n & 7;
                        if ((n & 15) == 0) { mbar_wait(bars + B_DEP + (n >> 4) * 8, 0); fence_async(); }
                        const int kvh = r < 2 ? 0 : (r - 2) * 16 + hd + 1;
                        mbar_wait(fb + 8, ((n >> 2) & 1) ^ 1);
                        mbar_expect_tx(fb, j == 0 ? 49152 : 32768);
                        bulk_g2s_mc(st + 16384 + rank * 16384, (rank ? g_V : g_K) + ((size_t)kvh * SEQ + j * 256) * 4, 16384, fb, 3);
                        if (j == 0) bulk_g2s(sb + OFF_Q, g_Q + ((size_t)(r * 16 + hd) * SEQ + rb * 256) * 4, 16384, fb);
                    }
                    const uint32_t target = lds32(bars + B_EPOCH) * 16;
                    const int br = cid >> 5;
                    for (int n = 0; n < 16; n++) {
                        const uint32_t fb = bars + 16 * (n & 3), st = sb + (n & 3) * SLOT;
                        mbar_wait(fb + 8, ((n >> 2) & 1) ^ 1);
                        mbar_expect_tx(fb, SLOT);
                        tma_ld_mc(st + 16384 + rank * 16384, br ? &mp.WoB : &mp.WoA, nb * 256 + rank * 128, n * 64, fb, 3);
                        tma_ld_mc(st + 24576 + rank * 16384, br ? &mp.WoB : &mp.WoA, nb * 256 + rank * 128 + 64, n * 64, fb, 3);
                        if ((n & 7) == 0) { cnt_wait(2 + (2 * br + (n >> 3)) * 8 + (cid & 7), target); fence_async(); }
                        tma_ld(st, &mp.O, n * 64, br * SEQ + mblk * 128, fb);
                    }
                }
            }
        } else if (wid == 17) {
            mbar_wait(bars + B_SIG, 0);
            if (lane == 0) cnt_signal(0);
            mbar_wait(bars + B_SIG, 1);
            if (small) {
                if (lane == 0) cnt_signal(0);
            } else {
                if (lane < 16) {
                    const int w = lane >> 2, h = lane & 3;
                    uint4* dst = (cid < 32 ? g_Q + (size_t)32 * SEQ * 4 : g_V + (size_t)SEQ * 4) + ((size_t)(nb * 8 + (w & 1) * 4 + h) * SEQ + mblk * 128 + (w >> 1) * 64) * 4;
                    bulk_s2g(dst, sb + (2 * (w & 1) + (h >> 1)) * SLOT + (w >> 1) * 8192 + (h & 1) * 4096, 4096);
                    asm volatile("cp.async.bulk.commit_group;\ncp.async.bulk.wait_group 0;" ::: "memory");
                    fence_async();
                }
                __syncwarp();
                if (lane == 0) cnt_signal(1);
                for (int r = 0; r < 4; r++) {
                    mbar_wait(bars + B_SIG, r & 1);
                    if (lane == 0) cnt_signal(2 + r * 8 + rb);
                }
            }
        } else if (wid == 18 && !small) {
            const uint32_t ep = __ldcg(g_epoch + blockIdx.x) + 1;
            __syncwarp();
            if (lane == 0) { g_epoch[blockIdx.x] = ep; sts32(bars + B_EPOCH, ep); }
            for (int half = 0; half < 2; half++) {
                cnt_wait(half, ep * (half ? 128 : 136));
                bool safe = true;
                for (int r = 2 * half; r < 2 * half + 2; r++) {
                    const int bh = r * 16 + hd, kvh = half ? bh - 31 : 0;
                    const uint32_t q = __ldcg((const uint32_t*)g_nrm + bh * 128 + rb * 16 + (lane & 15));
                    const uint4 k = __ldcg((const uint4*)(g_nrm + (64 + kvh) * 128) + lane);
                    const uint4 v = __ldcg((const uint4*)(g_nrm + (97 + kvh) * 128) + lane);
                    const float qm = __uint_as_float(__reduce_max_sync(0xffffffffu, q));
                    const float km = __uint_as_float(__reduce_max_sync(0xffffffffu, max(max(k.x, k.y), max(k.z, k.w))));
                    const float vm = __uint_as_float(__reduce_max_sync(0xffffffffu, max(max(v.x, v.y), max(v.z, v.w))));
                    safe = safe && (qm * km <= 3600.0f) && (vm <= 1.0e24f) && (vm >= 1.0e-24f);
                }
                if (lane == 0) { sts32(bars + B_FLAG + 4 * half, safe); mbar_arrive(bars + B_DEP + 8 * half); }
            }
        }
    } else {
        reg_inc<112>();
        const int warp = wid & 3, g = lane >> 2, c = lane & 3;
        if (small) {
            float acc[32];
#pragma unroll 1
            for (int n = 0; n < 32; n++) {
                const int s = n & 3;
                mbar_wait(bars + 16 * s, (n >> 2) & 1);
                const uint64_t da = mkdesc(sb + s * SLOT + wg * 8192, 16, 1024, 1);
                const uint64_t db = mkdesc(sb + s * SLOT + 32768, 4096, 512, 2);
                wg_fence();
#pragma unroll
                for (int k = 0; k < 4; k++) wgmma_ss_n64_t1(acc, da + 2 * k, db + 64 * k, (k > 0) ? 1 : (n & 15));
                wg_commit();
                wg_wait<0>();
                pin(acc);
                if (lane == 0) mbar_arrive(bars + 16 * s + 8);
                if ((n & 15) == 15) {
                    const int row = (blockIdx.x - 128) * 512 + (n >> 4) * 256 + wg * 64 + warp * 16 + g;
                    const int off = row * 4 + (c ^ ((row >> 1) & 3));
#pragma unroll
                    for (int h = 0; h < 2; h++) {
                        const float* v = &acc[16 * h];
                        uint4* dst = (h == 0 ? g_K : g_V) + off;
                        dst[0] = make_uint4(pack_bf16(v[0], v[1]), pack_bf16(v[4], v[5]), pack_bf16(v[8], v[9]), pack_bf16(v[12], v[13]));
                        dst[32] = make_uint4(pack_bf16(v[2], v[3]), pack_bf16(v[6], v[7]), pack_bf16(v[10], v[11]), pack_bf16(v[14], v[15]));
                        float a = 0.f, b = 0.f;
#pragma unroll
                        for (int j = 0; j < 4; j++) {
                            a = fmaf(v[4 * j], v[4 * j], fmaf(v[4 * j + 1], v[4 * j + 1], a));
                            b = fmaf(v[4 * j + 2], v[4 * j + 2], fmaf(v[4 * j + 3], v[4 * j + 3], b));
                        }
                        a += shx(a, 1); b += shx(b, 1);
                        a += shx(a, 2); b += shx(b, 2);
                        const uint32_t u = __reduce_max_sync(0xffffffffu, max(__float_as_uint(a), __float_as_uint(b)));
                        if (lane == 0) g_nrm[(h == 0 ? 64 : 97) * 128 + (row >> 4)] = __uint_as_float(u);
                    }
                    __syncwarp();
                    if (lane == 0) mbar_arrive(bars + B_SIG);
                    if (tid == 0) TL(0, 14 + (n >> 4));
                }
            }
        } else {
            const int mh = wg >> 1, nh = wg & 1;
            const uint32_t relbar = lane < 2 ? mapa(bars + 8, lane) : 0;
            const uint64_t da0 = mkdesc(sb + mh * 8192, 16, 1024, 1);
            const uint64_t db0 = mkdesc(sb + 16384 + nh * 16384, 8192, 1024, 1);
            const int rloc = warp * 16 + g;
            const int csw = c ^ ((g >> 1) & 3);
            {
                float acc[64];
                uint4 pk[8];
                const bool isQ = cid < 32;
                const float sc = isQ ? 0.25503486f : 1.0f;
                const int row = mblk * 128 + mh * 64 + rloc, h0 = nb * 8 + nh * 4;
#pragma unroll 1
                for (int kb = 0; kb < 16; kb++) { gemm_kstep(acc, sb, da0, db0, relbar, kb, kb > 0); if (kb == 0 && tid == 0) TL(0, 1); }
                wg_wait<0>();
                pin(acc);
                if (relbar) mbar_arrive_cluster(relbar + 48);
                if (tid == 0) TL(0, 2);
                proj_pack(acc, pk, sc, g_nrm + ((isQ ? 0 : 65) + h0) * 128 + (row >> 4), lane);
                if (tid == 0) TL(0, 3);
                uint4* dst = (isQ ? g_Q : g_K + (size_t)SEQ * 4) + ((size_t)h0 * SEQ + row) * 4 + csw;
#pragma unroll
                for (int i = 0; i < 4; i++) sts128(sb + OFF_Q + i * 8192 + tid * 16, pk[4 + i]);
#pragma unroll
                for (int kb = 0; kb < 8; kb++) {
                    gemm_kstep(acc, sb, da0, db0, relbar, kb, kb > 0);
                    dst[(kb >> 1) * SEQ * 4 + (kb & 1) * 32] = kb < 4 ? pk[kb] : lds128(sb + OFF_Q + (kb - 4) * 8192 + tid * 16);
                }
                __syncwarp();
                if (lane == 0) mbar_arrive(bars + B_SIG);
#pragma unroll 1
                for (int kb = 8; kb < 16; kb++) gemm_kstep(acc, sb, da0, db0, relbar, kb, true);
                wg_wait<0>();
                pin(acc);
                if (relbar) mbar_arrive_cluster(relbar + 48);
                if (tid == 0) TL(0, 4);
                proj_pack(acc, pk, sc, g_nrm + ((isQ ? 32 : 98) + h0) * 128 + (row >> 4), lane);
                asm volatile("bar.sync %0, 256;" ::"r"(1 + mh) : "memory");
#pragma unroll
                for (int i = 0; i < 8; i++)
                    sts128(sb + (2 * nh + (i >> 2)) * SLOT + mh * 8192 + ((i >> 1) & 1) * 4096 + (rloc + (i & 1) * 8) * 64 + csw * 16, pk[i]);
                fence_async_smem();
                __syncwarp();
                if (lane == 0) mbar_arrive(bars + B_SIG);
            }
            {
                const uint32_t qa = sb + OFF_Q + (wg * 64 + rloc) * 64 + (((g >> 1) & 3) << 4) + c * 4;
                uint4* op = g_O + ((size_t)rb * 256 + wg * 64 + rloc) * 128 + hd * 4 + c;
                int j = 0;
                mbar_wait(bars + B_DEP, 0);
                if (__all_sync(0xffffffffu, lds32(bars + B_FLAG))) j = attn_rounds<true>(sb, qa, relbar, op, 0, lane);
                if (j < 32) attn_rounds<false>(sb, qa, relbar, op, j, lane);
            }
            {
                float acc[64];
#pragma unroll 1
                for (int kb = 0; kb < 16; kb++) { gemm_kstep(acc, sb, da0, db0, relbar, kb, kb > 0 && kb <= 12); if (kb == 0 && tid == 0) TL(0, 10); }
                wg_wait<0>();
                pin(acc);
                if (tid == 0) TL(0, 11);
                asm volatile("bar.sync %0, 256;" ::"r"(1 + mh) : "memory");
                const int row = warp * 16 + (lane & 7) + ((lane >> 3) & 1) * 8;
#pragma unroll
                for (int ch = 0; ch < 2; ch++) {
                    const uint32_t base = sb + (2 * nh + ch) * SLOT + mh * 8192;
#pragma unroll
                    for (int jj = 0; jj < 4; jj++) {
                        const float* v = &acc[32 * ch + 8 * jj];
                        const uint32_t addr = base + row * 128 + (((2 * jj + (lane >> 4)) ^ (lane & 7)) << 4);
                        asm volatile("stmatrix.sync.aligned.m8n8.x4.shared.b16 [%0], {%1, %2, %3, %4};" ::"r"(addr), "r"(pack_bf16(v[0], v[1])), "r"(pack_bf16(v[2], v[3])),
                                     "r"(pack_bf16(v[4], v[5])), "r"(pack_bf16(v[6], v[7])) : "memory");
                    }
                    fence_async_smem();
                    __syncwarp();
                    if (lane == 0) {
                        tma_st(&mp.Out, base + warp * 2048, (cid >> 5) * 1024 + nb * 256 + nh * 128 + ch * 64, mblk * 128 + mh * 64 + warp * 16);
                        asm volatile("cp.async.bulk.commit_group;" ::: "memory");
                    }
                }
                if (tid == 0) TL(0, 12);
                if (lane == 0) asm volatile("cp.async.bulk.wait_group.read 0;" ::: "memory");
                if (tid == 0) TL(0, 13);
            }
        }
    }
}

typedef CUresult (*EncodeFn)(CUtensorMap*, CUtensorMapDataType, cuuint32_t, void*, const cuuint64_t*, const cuuint64_t*, const cuuint32_t*,
                             const cuuint32_t*, CUtensorMapInterleave, CUtensorMapSwizzle, CUtensorMapL2promotion, CUtensorMapFloatOOBfill);

static void make_map(EncodeFn enc, CUtensorMap* m, const void* p, int cols, int rows, int bx, int by, CUtensorMapSwizzle sw) {
    cuuint64_t dims[2] = {(cuuint64_t)cols, (cuuint64_t)rows};
    cuuint64_t strides[1] = {(cuuint64_t)cols * 2};
    cuuint32_t box[2] = {(cuuint32_t)bx, (cuuint32_t)by};
    cuuint32_t es[2] = {1, 1};
    enc(m, CU_TENSOR_MAP_DATA_TYPE_BFLOAT16, 2, (void*)p, dims, strides, box, es, CU_TENSOR_MAP_INTERLEAVE_NONE, sw,
        CU_TENSOR_MAP_L2_PROMOTION_L2_256B, CU_TENSOR_MAP_FLOAT_OOB_FILL_NONE);
}

extern "C" void kernel_launch(void* const* d_in, const int* in_sizes, int n_in, void* d_out, int out_size) {
    (void)in_sizes; (void)n_in; (void)out_size;
    void* fn = nullptr;
    cudaDriverEntryPointQueryResult qr;
    cudaGetDriverEntryPoint("cuTensorMapEncodeTiled", &fn, cudaEnableDefault, &qr);
    EncodeFn enc = (EncodeFn)fn;
    void* pO = nullptr;
    cudaGetSymbolAddress(&pO, g_O);
    Maps mp;
    make_map(enc, &mp.XA, d_in[0], 1024, 2048, 64, 128, CU_TENSOR_MAP_SWIZZLE_128B);
    make_map(enc, &mp.Wq, d_in[1], 1024, 1024, 64, 64, CU_TENSOR_MAP_SWIZZLE_128B);
    make_map(enc, &mp.Wk, d_in[2], 32, 1024, 32, 64, CU_TENSOR_MAP_SWIZZLE_64B);
    make_map(enc, &mp.Wv, d_in[3], 32, 1024, 32, 64, CU_TENSOR_MAP_SWIZZLE_64B);
    make_map(enc, &mp.WoA, d_in[4], 1024, 1024, 64, 64, CU_TENSOR_MAP_SWIZZLE_128B);
    make_map(enc, &mp.XB, d_in[5], 1024, 2048, 64, 128, CU_TENSOR_MAP_SWIZZLE_128B);
    make_map(enc, &mp.Wqkv, d_in[6], 3072, 1024, 64, 64, CU_TENSOR_MAP_SWIZZLE_128B);
    make_map(enc, &mp.WoB, d_in[7], 1024, 1024, 64, 64, CU_TENSOR_MAP_SWIZZLE_128B);
    make_map(enc, &mp.O, pO, 1024, 4096, 64, 128, CU_TENSOR_MAP_SWIZZLE_128B);
    make_map(enc, &mp.Out, d_out, 2048, 2048, 64, 16, CU_TENSOR_MAP_SWIZZLE_128B);
    cudaFuncSetAttribute(mega_kernel, cudaFuncAttributeMaxDynamicSharedMemorySize, SMEM_BYTES);
    mega_kernel<<<132, 640, SMEM_BYTES, cudaStreamPerThread>>>(mp);
}
```

```cpp
#include <cuda_runtime.h>
#include <cuda_bf16.h>
#include <cuda.h>
#include <stdint.h>

constexpr int SEQ = 2048;

__device__ __align__(1024) uint4 g_Q[64 * SEQ * 4];
__device__ __align__(1024) uint4 g_K[33 * SEQ * 4];
__device__ __align__(1024) uint4 g_Kh[33 * SEQ * 4];
__device__ __align__(1024) uint4 g_V[33 * SEQ * 4];
__device__ __align__(1024) uint4 g_O[2 * SEQ * 128];
__device__ __align__(16) float g_nrm[130 * 128];
__device__ unsigned g_cnt[36 * 32];
__device__ unsigned g_epoch[132];

__device__ __forceinline__ void wgmma_rs_n40_t1(float (&d)[20], uint32_t a0, uint32_t a1, uint32_t a2, uint32_t a3, uint64_t descB, int scaleD) {
    asm volatile("{\n.reg .pred p;\nsetp.ne.b32 p, %25, 0;\n"
        "wgmma.mma_async.sync.aligned.m64n40k16.f32.bf16.bf16 "
        "{%0, %1, %2, %3, %4, %5, %6, %7, %8, %9, %10, %11, %12, %13, %14, %15, "
        "%16, %17, %18, %19}, "
        "{%20, %21, %22, %23}, %24, p, 1, 1, 1;\n}\n"
        : "+f"(d[0]), "+f"(d[1]), "+f"(d[2]), "+f"(d[3]), "+f"(d[4]), "+f"(d[5]), "+f"(d[6]), "+f"(d[7]),
          "+f"(d[8]), "+f"(d[9]), "+f"(d[10]), "+f"(d[11]), "+f"(d[12]), "+f"(d[13]), "+f"(d[14]), "+f"(d[15]),
          "+f"(d[16]), "+f"(d[17]), "+f"(d[18]), "+f"(d[19])
        : "r"(a0), "r"(a1), "r"(a2), "r"(a3), "l"(descB), "r"(scaleD));
}
__device__ __forceinline__ void wgmma_ru_n64_t0(uint32_t (&d)[32], uint32_t a0, uint32_t a1, uint32_t a2, uint32_t a3, uint64_t descB, int scaleD) {
    asm volatile("{\n.reg .pred p;\nsetp.ne.b32 p, %37, 0;\n"
        "wgmma.mma_async.sync.aligned.m64n64k16.f32.bf16.bf16 "
        "{%0, %1, %2, %3, %4, %5, %6, %7, %8, %9, %10, %11, %12, %13, %14, %15, "
        "%16, %17, %18, %19, %20, %21, %22, %23, %24, %25, %26, %27, %28, %29, %30, %31}, "
        "{%32, %33, %34, %35}, %36, p, 1, 1, 0;\n}\n"
        : "+r"(d[0]), "+r"(d[1]), "+r"(d[2]), "+r"(d[3]), "+r"(d[4]), "+r"(d[5]), "+r"(d[6]), "+r"(d[7]),
          "+r"(d[8]), "+r"(d[9]), "+r"(d[10]), "+r"(d[11]), "+r"(d[12]), "+r"(d[13]), "+r"(d[14]), "+r"(d[15]),
          "+r"(d[16]), "+r"(d[17]), "+r"(d[18]), "+r"(d[19]), "+r"(d[20]), "+r"(d[21]), "+r"(d[22]), "+r"(d[23]),
          "+r"(d[24]), "+r"(d[25]), "+r"(d[26]), "+r"(d[27]), "+r"(d[28]), "+r"(d[29]), "+r"(d[30]), "+r"(d[31])
        : "r"(a0), "r"(a1), "r"(a2), "r"(a3), "l"(descB), "r"(scaleD));
}
__device__ __forceinline__ void wgmma_ss_n128_t1(float (&d)[64], uint64_t descA, uint64_t descB, int scaleD) {
    asm volatile("{\n.reg .pred p;\nsetp.ne.b32 p, %66, 0;\n"
        "wgmma.mma_async.sync.aligned.m64n128k16.f32.bf16.bf16 "
        "{%0, %1, %2, %3, %4, %5, %6, %7, %8, %9, %10, %11, %12, %13, %14, %15, "
        "%16, %17, %18, %19, %20, %21, %22, %23, %24, %25, %26, %27, %28, %29, %30, %31, "
        "%32, %33, %34, %35, %36, %37, %38, %39, %40, %41, %42, %43, %44, %45, %46, %47, "
        "%48, %49, %50, %51, %52, %53, %54, %55, %56, %57, %58, %59, %60, %61, %62, %63}, "
        "%64, %65, p, 1, 1, 0, 1;\n}\n"
        : "+f"(d[0]), "+f"(d[1]), "+f"(d[2]), "+f"(d[3]), "+f"(d[4]), "+f"(d[5]), "+f"(d[6]), "+f"(d[7]),
          "+f"(d[8]), "+f"(d[9]), "+f"(d[10]), "+f"(d[11]), "+f"(d[12]), "+f"(d[13]), "+f"(d[14]), "+f"(d[15]),
          "+f"(d[16]), "+f"(d[17]), "+f"(d[18]), "+f"(d[19]), "+f"(d[20]), "+f"(d[21]), "+f"(d[22]), "+f"(d[23]),
          "+f"(d[24]), "+f"(d[25]), "+f"(d[26]), "+f"(d[27]), "+f"(d[28]), "+f"(d[29]), "+f"(d[30]), "+f"(d[31]),
          "+f"(d[32]), "+f"(d[33]), "+f"(d[34]), "+f"(d[35]), "+f"(d[36]), "+f"(d[37]), "+f"(d[38]), "+f"(d[39]),
          "+f"(d[40]), "+f"(d[41]), "+f"(d[42]), "+f"(d[43]), "+f"(d[44]), "+f"(d[45]), "+f"(d[46]), "+f"(d[47]),
          "+f"(d[48]), "+f"(d[49]), "+f"(d[50]), "+f"(d[51]), "+f"(d[52]), "+f"(d[53]), "+f"(d[54]), "+f"(d[55]),
          "+f"(d[56]), "+f"(d[57]), "+f"(d[58]), "+f"(d[59]), "+f"(d[60]), "+f"(d[61]), "+f"(d[62]), "+f"(d[63])
        : "l"(descA), "l"(descB), "r"(scaleD));
}
__device__ __forceinline__ void wgmma_ss_n64_t1(float (&d)[32], uint64_t descA, uint64_t descB, int scaleD) {
    asm volatile("{\n.reg .pred p;\nsetp.ne.b32 p, %34, 0;\n"
        "wgmma.mma_async.sync.aligned.m64n64k16.f32.bf16.bf16 "
        "{%0, %1, %2, %3, %4, %5, %6, %7, %8, %9, %10, %11, %12, %13, %14, %15, "
        "%16, %17, %18, %19, %20, %21, %22, %23, %24, %25, %26, %27, %28, %29, %30, %31}, "
        "%32, %33, p, 1, 1, 0, 1;\n}\n"
        : "+f"(d[0]), "+f"(d[1]), "+f"(d[2]), "+f"(d[3]), "+f"(d[4]), "+f"(d[5]), "+f"(d[6]), "+f"(d[7]),
          "+f"(d[8]), "+f"(d[9]), "+f"(d[10]), "+f"(d[11]), "+f"(d[12]), "+f"(d[13]), "+f"(d[14]), "+f"(d[15]),
          "+f"(d[16]), "+f"(d[17]), "+f"(d[18]), "+f"(d[19]), "+f"(d[20]), "+f"(d[21]), "+f"(d[22]), "+f"(d[23]),
          "+f"(d[24]), "+f"(d[25]), "+f"(d[26]), "+f"(d[27]), "+f"(d[28]), "+f"(d[29]), "+f"(d[30]), "+f"(d[31])
        : "l"(descA), "l"(descB), "r"(scaleD));
}

__device__ __forceinline__ void wg_fence() { asm volatile("wgmma.fence.sync.aligned;" ::: "memory"); }
__device__ __forceinline__ void wg_commit() { asm volatile("wgmma.commit_group.sync.aligned;" ::: "memory"); }
template <int N> __device__ __forceinline__ void wg_wait() { asm volatile("wgmma.wait_group.sync.aligned %0;" ::"n"(N) : "memory"); }
template <int N> __device__ __forceinline__ void pin(float (&r)[N]) {
#pragma unroll
    for (int i = 0; i < N; i++) asm volatile("" : "+f"(r[i])::"memory");
}
template <int N> __device__ __forceinline__ void pin(uint32_t (&r)[N]) {
#pragma unroll
    for (int i = 0; i < N; i++) asm volatile("" : "+r"(r[i])::"memory");
}
__device__ __forceinline__ uint64_t mkdesc(uint32_t addr, uint32_t lbo, uint32_t sbo, int swz) {
    return (uint64_t)((addr & 0x3FFFF) >> 4) | ((uint64_t)((lbo >> 4) & 0x3FFF) << 16) | ((uint64_t)((sbo >> 4) & 0x3FFF) << 32) | ((uint64_t)swz << 62);
}
__device__ __forceinline__ uint32_t smem_u32(const void* p) { return (uint32_t)__cvta_generic_to_shared(p); }
__device__ __forceinline__ void mbar_init(uint32_t bar, uint32_t cnt) { asm volatile("mbarrier.init.shared::cta.b64 [%0], %1;" ::"r"(bar), "r"(cnt) : "memory"); }
__device__ __forceinline__ void mbar_arrive(uint32_t bar) { asm volatile("mbarrier.arrive.shared::cta.b64 _, [%0];" ::"r"(bar) : "memory"); }
__device__ __forceinline__ void mbar_arrive_cluster(uint32_t bar) { asm volatile("mbarrier.arrive.shared::cluster.b64 _, [%0];" ::"r"(bar) : "memory"); }
__device__ __forceinline__ void mbar_expect_tx(uint32_t bar, uint32_t bytes) { asm volatile("mbarrier.arrive.expect_tx.shared::cta.b64 _, [%0], %1;" ::"r"(bar), "r"(bytes) : "memory"); }
__device__ __forceinline__ void mbar_wait(uint32_t bar, uint32_t parity) {
    asm volatile("{\n.reg .pred p;\n.reg .u32 cnt;\n"
                 "mbarrier.try_wait.parity.shared::cta.b64 p, [%0], %1;\n"
                 "@p bra LAB_DONE;\n"
                 "mov.u32 cnt, 0;\nLAB_WAIT:\n"
                 "mbarrier.try_wait.parity.shared::cta.b64 p, [%0], %1;\n"
                 "@p bra LAB_DONE;\n"
                 "add.u32 cnt, cnt, 1;\n"
                 "setp.lt.u32 p, cnt, 0x1000000;\n"
                 "@p bra LAB_WAIT;\n"
                 "trap;\n"
                 "LAB_DONE:\n}\n" ::"r"(bar), "r"(parity) : "memory");
}
__device__ __forceinline__ void mbar_wait_idle(uint32_t bar, uint32_t parity) {
    asm volatile("{\n.reg .pred p;\n.reg .u32 cnt;\nmov.u32 cnt, 0;\nLAB_WAIT:\n"
                 "mbarrier.try_wait.parity.shared::cta.b64 p, [%0], %1, 100000;\n"
                 "@p bra LAB_DONE;\n"
                 "add.u32 cnt, cnt, 1;\n"
                 "setp.lt.u32 p, cnt, 0x8000;\n"
                 "@p bra LAB_WAIT;\n"
                 "trap;\n"
                 "LAB_DONE:\n}\n" ::"r"(bar), "r"(parity) : "memory");
}
__device__ __forceinline__ uint32_t mapa(uint32_t addr, uint32_t rank) { uint32_t r; asm("mapa.shared::cluster.u32 %0, %1, %2;" : "=r"(r) : "r"(addr), "r"(rank)); return r; }
__device__ __forceinline__ void bulk_g2s(uint32_t dst, const void* src, uint32_t bytes, uint32_t bar) {
    asm volatile("cp.async.bulk.shared::cluster.global.mbarrier::complete_tx::bytes [%0], [%1], %2, [%3];" ::"r"(dst), "l"(src), "r"(bytes), "r"(bar) : "memory");
}
__device__ __forceinline__ void tma_ld(uint32_t dst, const CUtensorMap* m, int x, int y, uint32_t bar) {
    asm volatile("cp.async.bulk.tensor.2d.shared::cluster.global.mbarrier::complete_tx::bytes [%0], [%1, {%3, %4}], [%2];" ::"r"(dst), "l"(m), "r"(bar), "r"(x), "r"(y) : "memory");
}
__device__ __forceinline__ void tma_ld_mc(uint32_t dst, const CUtensorMap* m, int x, int y, uint32_t bar, uint16_t mask) {
    asm volatile("cp.async.bulk.tensor.2d.shared::cluster.global.mbarrier::complete_tx::bytes.multicast::cluster [%0], [%1, {%3, %4}], [%2], %5;" ::"r"(dst), "l"(m), "r"(bar), "r"(x), "r"(y), "h"(mask) : "memory");
}
__device__ __forceinline__ void tma_st(const CUtensorMap* m, uint32_t src, int x, int y) {
    asm volatile("cp.async.bulk.tensor.2d.global.shared::cta.bulk_group [%0, {%2, %3}], [%1];" ::"l"(m), "r"(src), "r"(x), "r"(y) : "memory");
}
__device__ __forceinline__ void tma_pf(const CUtensorMap* m, int x, int y) { asm volatile("cp.async.bulk.prefetch.tensor.2d.L2.global [%0, {%1, %2}];" ::"l"(m), "r"(x), "r"(y) : "memory"); }
__device__ __forceinline__ void prefetch_tmap(const CUtensorMap* m) { asm volatile("prefetch.tensormap [%0];" ::"l"(m) : "memory"); }
__device__ __forceinline__ void bulk_g2s_mc(uint32_t dst, const void* src, uint32_t bytes, uint32_t bar, uint16_t mask) {
    asm volatile("cp.async.bulk.shared::cluster.global.mbarrier::complete_tx::bytes.multicast::cluster [%0], [%1], %2, [%3], %4;" ::"r"(dst), "l"(src), "r"(bytes), "r"(bar), "h"(mask) : "memory");
}
__device__ __forceinline__ void bulk_s2g(void* dst, uint32_t src, uint32_t bytes) {
    asm volatile("cp.async.bulk.global.shared::cta.bulk_group [%0], [%1], %2;" ::"l"(dst), "r"(src), "r"(bytes) : "memory");
}
__device__ __forceinline__ void fence_async() { asm volatile("fence.proxy.async;" ::: "memory"); }
__device__ __forceinline__ void fence_async_smem() { asm volatile("fence.proxy.async.shared::cta;" ::: "memory"); }
__device__ __forceinline__ void cnt_signal(int idx) { asm volatile("fence.acq_rel.gpu;\nred.relaxed.gpu.global.add.u32 [%0], 1;" ::"l"(g_cnt + idx * 32) : "memory"); }
__device__ __forceinline__ void cnt_wait(int idx, uint32_t target, uint32_t ns = 64) {
    for (int it = 0;; it++) {
        uint32_t v;
        asm volatile("ld.acquire.gpu.global.u32 %0, [%1];" : "=r"(v) : "l"(g_cnt + idx * 32) : "memory");
        if ((int)(v - target) >= 0) break;
        if (it > (1 << 21)) __trap();
        __nanosleep(ns);
    }
}
__device__ __forceinline__ uint32_t lds32(uint32_t a) { uint32_t v; asm volatile("ld.shared.u32 %0, [%1];" : "=r"(v) : "r"(a) : "memory"); return v; }
__device__ __forceinline__ void sts32(uint32_t a, uint32_t v) { asm volatile("st.shared.u32 [%0], %1;" ::"r"(a), "r"(v) : "memory"); }
__device__ __forceinline__ void sts128(uint32_t a, uint4 v) { asm volatile("st.shared.v4.u32 [%0], {%1, %2, %3, %4};" ::"r"(a), "r"(v.x), "r"(v.y), "r"(v.z), "r"(v.w) : "memory"); }
__device__ __forceinline__ uint4 lds128(uint32_t a) { uint4 v; asm volatile("ld.shared.v4.u32 {%0, %1, %2, %3}, [%4];" : "=r"(v.x), "=r"(v.y), "=r"(v.z), "=r"(v.w) : "r"(a) : "memory"); return v; }
__device__ __forceinline__ float shx(float v, int m) { return __shfl_xor_sync(0xffffffffu, v, m); }
__device__ __forceinline__ float ex2f(float x) { float y; asm("ex2.approx.ftz.f32 %0, %1;" : "=f"(y) : "f"(x)); return y; }
__device__ __forceinline__ float rcpf(float x) { float y; asm("rcp.approx.ftz.f32 %0, %1;" : "=f"(y) : "f"(x)); return y; }
__device__ __forceinline__ uint32_t pack_bf16(float lo, float hi) { uint32_t r; asm("cvt.rn.bf16x2.f32 %0, %1, %2;" : "=r"(r) : "f"(hi), "f"(lo)); return r; }
template <int R> __device__ __forceinline__ void reg_inc() { asm volatile("setmaxnreg.inc.sync.aligned.u32 %0;" ::"n"(R)); }
template <int R> __device__ __forceinline__ void reg_dec() { asm volatile("setmaxnreg.dec.sync.aligned.u32 %0;" ::"n"(R)); }

constexpr int SLOT = 49152;
constexpr int OFF_Q = 4 * SLOT;
constexpr int OFF_ONES = OFF_Q + 32768;
constexpr int OFF_BAR = OFF_ONES + 1024;
constexpr int SMEM_BYTES = OFF_BAR + 256 + 1024;
constexpr int B_AF = 64, B_AE = 128, B_SIG = 192, B_DEP = 200, B_FLAG = 224, B_EPOCH = 232;
constexpr int OFF_K0 = 8192;

__device__ __forceinline__ uint64_t gdesc(uint32_t lo) { return ((uint64_t)((1024 >> 4) | (1u << 30)) << 32) | lo; }
__device__ __forceinline__ void gemm_kstep(float (&acc)[64], uint32_t sb, uint32_t da0, uint32_t db0, uint32_t relbar, int kb, bool rel) {
    const int s = kb & 3;
    mbar_wait(sb + OFF_BAR + 16 * s, (kb >> 2) & 1);
    const uint64_t da = gdesc(da0 + s * (SLOT / 16)), db = gdesc(db0 + s * (SLOT / 16));
    wg_fence();
#pragma unroll
    for (int k = 0; k < 4; k++) wgmma_ss_n128_t1(acc, da + 2 * k, db + 128 * k, (k > 0) ? 1 : kb);
    wg_commit();
    wg_wait<1>();
    if (rel && relbar) mbar_arrive_cluster(relbar + 16 * ((kb - 1) & 3));
}

__device__ __forceinline__ void bar_sync(int id, int n) { asm volatile("bar.sync %0, %1;" ::"r"(id), "r"(n) : "memory"); }
__device__ __forceinline__ void bar_arrive(int id, int n) { asm volatile("bar.arrive %0, %1;" ::"r"(id), "r"(n) : "memory"); }
template <int NB, int REL>
__device__ __forceinline__ void gemm_finish(float (&acc)[64], uint32_t sb, uint32_t da0, uint32_t db0, uint32_t relbar, int wg) {
    constexpr int K0 = 16 - NB;
    if (wg > 0) {
        wg_wait<0>();
        if (K0 - 1 <= REL && relbar) mbar_arrive_cluster(relbar + 16 * ((K0 - 1) & 3));
        bar_sync(wg, 256);
    }
#pragma unroll 1
    for (int kb = K0; kb < 16; kb++) {
        const int s = kb & 3;
        mbar_wait(sb + OFF_BAR + 16 * s, 1);
        const uint64_t da = gdesc(da0 + s * (SLOT / 16)), db = gdesc(db0 + s * (SLOT / 16));
        wg_fence();
#pragma unroll
        for (int k = 0; k < 4; k++) wgmma_ss_n128_t1(acc, da + 2 * k, db + 128 * k, 1);
        wg_commit();
        if (kb == K0 && wg == 0) {
            wg_wait<1>();
            if (K0 - 1 <= REL && relbar) mbar_arrive_cluster(relbar + 16 * ((K0 - 1) & 3));
        }
    }
    if (wg < 3) bar_arrive(wg + 1, 256);
    if (NB >= 3) { wg_wait<2>(); if (13 <= REL && relbar) mbar_arrive_cluster(relbar + 16); }
    if (NB >= 2) { wg_wait<1>(); if (14 <= REL && relbar) mbar_arrive_cluster(relbar + 32); }
    wg_wait<0>();
    pin(acc);
    if (15 <= REL && relbar) mbar_arrive_cluster(relbar + 48);
}
__device__ __forceinline__ uint32_t stage_addr(uint32_t sb, int wg, int half) {
    return wg == 0 ? sb + OFF_Q + 16384 + half * 8192 : sb + ((wg == 1 ? 0 : 2) + half) * SLOT + (wg == 3 ? 8192 : 0);
}
__device__ __forceinline__ void stage_acquire(int wg) {
    if (wg > 0) bar_sync(4 + wg, 256);
    if (wg < 3) bar_arrive(5 + wg, 256);
}

template <bool ISQ>
__device__ __forceinline__ void proj_pack(const float (&acc)[64], uint4 (&pk)[8], float (&ss)[8]) {
#pragma unroll
    for (int h = 0; h < 8; h++) {
        float v[8];
#pragma unroll
        for (int i = 0; i < 8; i++) v[i] = acc[16 * (h >> 1) + 2 * (h & 1) + 4 * (i >> 1) + (i & 1)] * (ISQ ? 0.25503486f : 1.0f);
        pk[h] = make_uint4(pack_bf16(v[0], v[1]), pack_bf16(v[2], v[3]), pack_bf16(v[4], v[5]), pack_bf16(v[6], v[7]));
        asm volatile("" : "+r"(pk[h].x), "+r"(pk[h].y), "+r"(pk[h].z), "+r"(pk[h].w)::"memory");
        if (!ISQ) {
            float a = v[0] * v[0];
#pragma unroll
            for (int i = 1; i < 8; i++) a = fmaf(v[i], v[i], a);
            ss[h] = a;
        }
    }
}
__device__ __forceinline__ float sumsq(uint4 p) {
    const uint32_t w[4] = {p.x, p.y, p.z, p.w};
    float a = 0.f;
#pragma unroll
    for (int i = 0; i < 4; i++) {
        const float lo = __uint_as_float(w[i] << 16), hi = __uint_as_float(w[i] & 0xFFFF0000u);
        a = fmaf(lo, lo, fmaf(hi, hi, a));
    }
    return a;
}
__device__ __forceinline__ void publish_norms(const float (&ss)[8], float* nrm, int lane) {
    const int c = lane & 3;
    float t4[4], t2[2];
#pragma unroll
    for (int h = 0; h < 4; h++) t4[h] = ((c & 1) ? ss[2 * h + 1] : ss[2 * h]) + shx((c & 1) ? ss[2 * h] : ss[2 * h + 1], 1);
#pragma unroll
    for (int h = 0; h < 2; h++) t2[h] = ((c & 2) ? t4[2 + h] : t4[h]) + shx((c & 2) ? t4[h] : t4[2 + h], 2);
    uint32_t u = max(__float_as_uint((c & 1) ? t2[1] : t2[0]), __float_as_uint(shx((c & 1) ? t2[0] : t2[1], 1)));
    u = max(u, __shfl_xor_sync(0xffffffffu, u, 4));
    u = max(u, __shfl_xor_sync(0xffffffffu, u, 8));
    u = max(u, __shfl_xor_sync(0xffffffffu, u, 16));
    *nrm = __uint_as_float(u);
}

constexpr int NP = 8, NS = 24;
__device__ __forceinline__ void attn_round_asm(uint32_t (&S)[NS], uint32_t (&P)[16], uint32_t (&T)[NP], float (&O)[20], uint32_t (&Q)[8], uint32_t c_al,
        uint32_t v0, uint32_t ja0, uint32_t par, uint32_t rel, uint32_t never, uint32_t qa, uint32_t c_m) {
    asm volatile(
        "{\n.reg .pred p, pr, pt, pf, pl;\n.reg .b32 y, c0, c1, c2, c3, cm, v, ja, jr, t, cnt, h1;\n.reg .b64 d<8>, dv;\nadd.u32 h1, %81, 0x80000020;\n"
        "mov.b32 cm, 0x4fa04fa0;\nmov.b32 c3, 0x4a584a58;\nmov.b32 c2, 0x21c021c0;\nmov.b32 c1, 0x12221222;\nmov.b32 c0, 0x0a950a95;\nsetp.ne.u32 pr, %80, 0;\n"
        "setp.eq.u32 pt, 0, 0;\nsetp.ne.u32 pf, 0, 0;\nmov.b32 ja, %78;\n"
        "LOOP:\nmbarrier.try_wait.parity.shared::cta.b64 p, [ja], %79;\nand.b32 t, ja, 24;\nadd.u32 ja, ja, 8;\nmad.lo.u32 v, t, 4269801856, %77;\n"
        "and.b32 t, ja, 56;\nsetp.ne.u32 pl, t, 0;\n@!p bra.uni SLOW;\n"
        "BACK:\nwgmma.wait_group.sync.aligned 0;\nfma.rn.f16x2 %7, %83, cm, %23;\nex2.approx.ftz.f32 %28, %28;\nfma.rn.f16x2 %47, %7, %76, c3;\n"
        "fma.rn.f16x2 %4, %83, cm, %20;\nfma.rn.f16x2 %2, %83, cm, %18;\nfma.rn.f16x2 %44, %4, %76, c3;\n"
        "L0_1:\nfma.rn.f16x2 %44, %20, c2, %44;\nex2.approx.ftz.f32 %29, %29;\nfma.rn.f16x2 %47, %23, c2, %47;\nfma.rn.f16x2 %42, %2, %76, c3;\n"
        "L0_2:\nex2.approx.ftz.f32 %36, %36;\nfma.rn.f16x2 %23, %47, %47, c1;\nfma.rn.f16x2 %20, %44, %44, c1;\n"
        "L0_3:\nfma.rn.f16x2 %42, %18, c2, %42;\nfma.rn.f16x2 %44, %20, %44, c0;\nex2.approx.ftz.f32 %37, %37;\ncvt.rn.bf16x2.f32 %10, %29, %28;\n"
        "L0_4:\nfma.rn.f16x2 %18, %42, %42, c1;\nex2.approx.ftz.f32 %32, %32;\nfma.rn.f16x2 %47, %23, %47, c0;\nshf.l.wrap.b32 y, %4, %4, 7;\n"
        "add.u32 %4, y, %44;\n"
        "L0_5:\nfma.rn.f16x2 %42, %18, %42, c0;\nex2.approx.ftz.f32 %33, %33;\ncvt.rn.bf16x2.f32 %14, %37, %36;\nshf.l.wrap.b32 y, %2, %2, 7;\n"
        "add.u32 %2, y, %42;\nshf.l.wrap.b32 y, %7, %7, 7;\nadd.u32 %7, y, %47;\nfma.rn.f16x2 %5, %83, cm, %21;\nfma.rn.f16x2 %0, %83, cm, %16;\n"
        "fma.rn.f16x2 %3, %83, cm, %19;\nfma.rn.f16x2 %45, %5, %76, c3;\nex2.approx.ftz.f32 %26, %26;\n"
        "L0_6:\nex2.approx.ftz.f32 %27, %27;\ncvt.rn.bf16x2.f32 %12, %33, %32;\nfma.rn.f16x2 %40, %0, %76, c3;\nfma.rn.f16x2 %1, %83, cm, %17;\n"
        "fma.rn.f16x2 %45, %21, c2, %45;\nfma.rn.f16x2 %40, %16, c2, %40;\nfma.rn.f16x2 %41, %1, %76, c3;\nex2.approx.ftz.f32 %34, %34;\n"
        "L0_7:\nex2.approx.ftz.f32 %35, %35;\nfma.rn.f16x2 %21, %45, %45, c1;\nfma.rn.f16x2 %16, %40, %40, c1;\nex2.approx.ftz.f32 %38, %38;\n"
        "fma.rn.f16x2 %40, %16, %40, c0;\nfma.rn.f16x2 %45, %21, %45, c0;\nfma.rn.f16x2 %41, %17, c2, %41;\nshf.l.wrap.b32 y, %0, %0, 7;\nadd.u32 %0, y, %40;\n"
        "cvt.rn.bf16x2.f32 %13, %35, %34;\n"
        "L0_8:\nshf.l.wrap.b32 y, %5, %5, 7;\nadd.u32 %5, y, %45;\nfma.rn.f16x2 %6, %83, cm, %22;\nex2.approx.ftz.f32 %39, %39;\n"
        "cvt.rn.bf16x2.f32 %9, %27, %26;\n"
        "L0_9:\nfma.rn.f16x2 %43, %3, %76, c3;\nfma.rn.f16x2 %17, %41, %41, c1;\nex2.approx.ftz.f32 %24, %24;\nex2.approx.ftz.f32 %25, %25;\n"
        "L0_10:\nfma.rn.f16x2 %41, %17, %41, c0;\nfma.rn.f16x2 %43, %19, c2, %43;\n"
        "L0_11:\nfma.rn.f16x2 %46, %6, %76, c3;\nshf.l.wrap.b32 y, %1, %1, 7;\nadd.u32 %1, y, %41;\ncvt.rn.bf16x2.f32 %15, %39, %38;\n"
        "ex2.approx.ftz.f32 %30, %30;\n"
        "L0_12:\nfma.rn.f16x2 %19, %43, %43, c1;\n"
        "L0_13:\nfma.rn.f16x2 %46, %22, c2, %46;\ncvt.rn.bf16x2.f32 %8, %25, %24;\nex2.approx.ftz.f32 %31, %31;\nfma.rn.f16x2 %22, %46, %46, c1;\n"
        "L0_14:\nfma.rn.f16x2 %46, %22, %46, c0;\n"
        "L0_15:\nfma.rn.f16x2 %43, %19, %43, c0;\nshf.l.wrap.b32 y, %3, %3, 7;\nadd.u32 %3, y, %43;\nshf.l.wrap.b32 y, %6, %6, 7;\nadd.u32 %6, y, %46;\n"
        "mov.b64 dv, {v, h1};\nadd.s64 d7, dv, -12582720;\nwgmma.fence.sync.aligned;\n"
        "wgmma.mma_async.sync.aligned.m64n40k16.f32.bf16.bf16 {%48, %49, %50, %51, %52, %53, %54, %55, %56, %57, %58, %59, %60, %61, %62, %63, %64, %65, %66, %67}, {%12, %13, %14, %15}, d7, pt, 1, 1, 1;\n"
        "L0_16:\ncvt.rn.bf16x2.f32 %11, %31, %30;\nmov.b64 dv, {v, h1};\nadd.s64 d2, dv, -896;\nadd.s64 d5, dv, -4194240;\nadd.s64 d6, dv, -8388480;\n"
        "add.s64 d3, dv, -894;\nadd.s64 d0, dv, -1024;\nadd.s64 d1, dv, -1022;\nadd.s64 d4, dv, 0;\nwgmma.fence.sync.aligned;\n"
        "wgmma.mma_async.sync.aligned.m64n32k16.f32.f16.f16 {%24, %25, %26, %27, %28, %29, %30, %31, %32, %33, %34, %35, %36, %37, %38, %39}, {%68, %69, %70, %71}, d2, pf, 1, 1, 0;\n"
        "wgmma.mma_async.sync.aligned.m64n40k16.f32.bf16.bf16 {%48, %49, %50, %51, %52, %53, %54, %55, %56, %57, %58, %59, %60, %61, %62, %63, %64, %65, %66, %67}, {%4, %5, %6, %7}, d5, pt, 1, 1, 1;\n"
        "wgmma.mma_async.sync.aligned.m64n40k16.f32.bf16.bf16 {%48, %49, %50, %51, %52, %53, %54, %55, %56, %57, %58, %59, %60, %61, %62, %63, %64, %65, %66, %67}, {%8, %9, %10, %11}, d6, pt, 1, 1, 1;\n"
        "wgmma.mma_async.sync.aligned.m64n32k16.f32.f16.f16 {%24, %25, %26, %27, %28, %29, %30, %31, %32, %33, %34, %35, %36, %37, %38, %39}, {%72, %73, %74, %75}, d3, pt, 1, 1, 0;\n"
        "wgmma.mma_async.sync.aligned.m64n32k16.f16.f16.f16 {%16, %17, %18, %19, %20, %21, %22, %23}, {%68, %69, %70, %71}, d0, pf, 1, 1, 0;\n"
        "wgmma.mma_async.sync.aligned.m64n32k16.f16.f16.f16 {%16, %17, %18, %19, %20, %21, %22, %23}, {%72, %73, %74, %75}, d1, pt, 1, 1, 0;\n"
        "wgmma.mma_async.sync.aligned.m64n40k16.f32.bf16.bf16 {%48, %49, %50, %51, %52, %53, %54, %55, %56, %57, %58, %59, %60, %61, %62, %63, %64, %65, %66, %67}, {%0, %1, %2, %3}, d4, pt, 1, 1, 1;\n"
        "wgmma.commit_group.sync.aligned;\nadd.u32 jr, ja, %80;\n@pr mbarrier.arrive.shared::cluster.b64 _, [jr+-8];\nwgmma.wait_group.sync.aligned 0;\n"
        "fma.rn.f16x2 %7, %83, cm, %23;\nex2.approx.ftz.f32 %28, %28;\nfma.rn.f16x2 %47, %7, %76, c3;\nfma.rn.f16x2 %4, %83, cm, %20;\n"
        "fma.rn.f16x2 %2, %83, cm, %18;\nfma.rn.f16x2 %44, %4, %76, c3;\n"
        "L1_1:\nfma.rn.f16x2 %44, %20, c2, %44;\nex2.approx.ftz.f32 %29, %29;\nfma.rn.f16x2 %47, %23, c2, %47;\nfma.rn.f16x2 %42, %2, %76, c3;\n"
        "L1_2:\nex2.approx.ftz.f32 %36, %36;\nfma.rn.f16x2 %23, %47, %47, c1;\nfma.rn.f16x2 %20, %44, %44, c1;\n"
        "L1_3:\nfma.rn.f16x2 %42, %18, c2, %42;\nfma.rn.f16x2 %44, %20, %44, c0;\nex2.approx.ftz.f32 %37, %37;\ncvt.rn.bf16x2.f32 %10, %29, %28;\n"
        "L1_4:\nfma.rn.f16x2 %18, %42, %42, c1;\nex2.approx.ftz.f32 %32, %32;\nfma.rn.f16x2 %47, %23, %47, c0;\nshf.l.wrap.b32 y, %4, %4, 7;\n"
        "add.u32 %4, y, %44;\n"
        "L1_5:\nfma.rn.f16x2 %42, %18, %42, c0;\nex2.approx.ftz.f32 %33, %33;\ncvt.rn.bf16x2.f32 %14, %37, %36;\nshf.l.wrap.b32 y, %2, %2, 7;\n"
        "add.u32 %2, y, %42;\nshf.l.wrap.b32 y, %7, %7, 7;\nadd.u32 %7, y, %47;\nfma.rn.f16x2 %5, %83, cm, %21;\nfma.rn.f16x2 %0, %83, cm, %16;\n"
        "fma.rn.f16x2 %3, %83, cm, %19;\nfma.rn.f16x2 %45, %5, %76, c3;\nex2.approx.ftz.f32 %26, %26;\n"
        "L1_6:\nex2.approx.ftz.f32 %27, %27;\ncvt.rn.bf16x2.f32 %12, %33, %32;\nfma.rn.f16x2 %40, %0, %76, c3;\nfma.rn.f16x2 %1, %83, cm, %17;\n"
        "fma.rn.f16x2 %45, %21, c2, %45;\nfma.rn.f16x2 %40, %16, c2, %40;\nfma.rn.f16x2 %41, %1, %76, c3;\nex2.approx.ftz.f32 %34, %34;\n"
        "L1_7:\nex2.approx.ftz.f32 %35, %35;\nfma.rn.f16x2 %21, %45, %45, c1;\nfma.rn.f16x2 %16, %40, %40, c1;\nex2.approx.ftz.f32 %38, %38;\n"
        "fma.rn.f16x2 %40, %16, %40, c0;\nfma.rn.f16x2 %45, %21, %45, c0;\nfma.rn.f16x2 %41, %17, c2, %41;\nshf.l.wrap.b32 y, %0, %0, 7;\nadd.u32 %0, y, %40;\n"
        "cvt.rn.bf16x2.f32 %13, %35, %34;\n"
        "L1_8:\nshf.l.wrap.b32 y, %5, %5, 7;\nadd.u32 %5, y, %45;\nfma.rn.f16x2 %6, %83, cm, %22;\nex2.approx.ftz.f32 %39, %39;\n"
        "cvt.rn.bf16x2.f32 %9, %27, %26;\n"
        "L1_9:\nfma.rn.f16x2 %43, %3, %76, c3;\nfma.rn.f16x2 %17, %41, %41, c1;\nex2.approx.ftz.f32 %24, %24;\nex2.approx.ftz.f32 %25, %25;\n"
        "L1_10:\nfma.rn.f16x2 %41, %17, %41, c0;\nfma.rn.f16x2 %43, %19, c2, %43;\n"
        "L1_11:\nfma.rn.f16x2 %46, %6, %76, c3;\nshf.l.wrap.b32 y, %1, %1, 7;\nadd.u32 %1, y, %41;\ncvt.rn.bf16x2.f32 %15, %39, %38;\n"
        "ex2.approx.ftz.f32 %30, %30;\n"
        "L1_12:\nfma.rn.f16x2 %19, %43, %43, c1;\n"
        "L1_13:\nfma.rn.f16x2 %46, %22, c2, %46;\ncvt.rn.bf16x2.f32 %8, %25, %24;\nex2.approx.ftz.f32 %31, %31;\nfma.rn.f16x2 %22, %46, %46, c1;\n"
        "L1_14:\nfma.rn.f16x2 %46, %22, %46, c0;\n"
        "L1_15:\nfma.rn.f16x2 %43, %19, %43, c0;\nshf.l.wrap.b32 y, %3, %3, 7;\nadd.u32 %3, y, %43;\nshf.l.wrap.b32 y, %6, %6, 7;\nadd.u32 %6, y, %46;\n"
        "mov.b64 dv, {v, h1};\nadd.s64 d7, dv, -29359680;\nwgmma.fence.sync.aligned;\n"
        "wgmma.mma_async.sync.aligned.m64n40k16.f32.bf16.bf16 {%48, %49, %50, %51, %52, %53, %54, %55, %56, %57, %58, %59, %60, %61, %62, %63, %64, %65, %66, %67}, {%12, %13, %14, %15}, d7, pt, 1, 1, 1;\n"
        "L1_16:\ncvt.rn.bf16x2.f32 %11, %31, %30;\nmov.b64 dv, {v, h1};\nadd.s64 d2, dv, -640;\nadd.s64 d5, dv, -20971200;\nadd.s64 d6, dv, -25165440;\n"
        "add.s64 d3, dv, -638;\nadd.s64 d0, dv, -768;\nadd.s64 d1, dv, -766;\nadd.s64 d4, dv, -16776960;\nwgmma.fence.sync.aligned;\n"
        "wgmma.mma_async.sync.aligned.m64n32k16.f32.f16.f16 {%24, %25, %26, %27, %28, %29, %30, %31, %32, %33, %34, %35, %36, %37, %38, %39}, {%68, %69, %70, %71}, d2, pf, 1, 1, 0;\n"
        "wgmma.mma_async.sync.aligned.m64n40k16.f32.bf16.bf16 {%48, %49, %50, %51, %52, %53, %54, %55, %56, %57, %58, %59, %60, %61, %62, %63, %64, %65, %66, %67}, {%4, %5, %6, %7}, d5, pt, 1, 1, 1;\n"
        "wgmma.mma_async.sync.aligned.m64n40k16.f32.bf16.bf16 {%48, %49, %50, %51, %52, %53, %54, %55, %56, %57, %58, %59, %60, %61, %62, %63, %64, %65, %66, %67}, {%8, %9, %10, %11}, d6, pt, 1, 1, 1;\n"
        "wgmma.mma_async.sync.aligned.m64n32k16.f32.f16.f16 {%24, %25, %26, %27, %28, %29, %30, %31, %32, %33, %34, %35, %36, %37, %38, %39}, {%72, %73, %74, %75}, d3, pt, 1, 1, 0;\n"
        "wgmma.mma_async.sync.aligned.m64n32k16.f16.f16.f16 {%16, %17, %18, %19, %20, %21, %22, %23}, {%68, %69, %70, %71}, d0, pf, 1, 1, 0;\n"
        "wgmma.mma_async.sync.aligned.m64n32k16.f16.f16.f16 {%16, %17, %18, %19, %20, %21, %22, %23}, {%72, %73, %74, %75}, d1, pt, 1, 1, 0;\n"
        "wgmma.mma_async.sync.aligned.m64n40k16.f32.bf16.bf16 {%48, %49, %50, %51, %52, %53, %54, %55, %56, %57, %58, %59, %60, %61, %62, %63, %64, %65, %66, %67}, {%0, %1, %2, %3}, d4, pt, 1, 1, 1;\n"
        "wgmma.commit_group.sync.aligned;\nwgmma.wait_group.sync.aligned 0;\nfma.rn.f16x2 %7, %83, cm, %23;\nex2.approx.ftz.f32 %28, %28;\n"
        "fma.rn.f16x2 %47, %7, %76, c3;\nfma.rn.f16x2 %4, %83, cm, %20;\nfma.rn.f16x2 %2, %83, cm, %18;\nfma.rn.f16x2 %44, %4, %76, c3;\n"
        "L2_1:\nfma.rn.f16x2 %44, %20, c2, %44;\nex2.approx.ftz.f32 %29, %29;\nfma.rn.f16x2 %47, %23, c2, %47;\nfma.rn.f16x2 %42, %2, %76, c3;\n"
        "L2_2:\nex2.approx.ftz.f32 %36, %36;\nfma.rn.f16x2 %23, %47, %47, c1;\nfma.rn.f16x2 %20, %44, %44, c1;\n"
        "L2_3:\nfma.rn.f16x2 %42, %18, c2, %42;\nfma.rn.f16x2 %44, %20, %44, c0;\nex2.approx.ftz.f32 %37, %37;\ncvt.rn.bf16x2.f32 %10, %29, %28;\n"
        "L2_4:\nfma.rn.f16x2 %18, %42, %42, c1;\nex2.approx.ftz.f32 %32, %32;\nfma.rn.f16x2 %47, %23, %47, c0;\nshf.l.wrap.b32 y, %4, %4, 7;\n"
        "add.u32 %4, y, %44;\n"
        "L2_5:\nfma.rn.f16x2 %42, %18, %42, c0;\nex2.approx.ftz.f32 %33, %33;\ncvt.rn.bf16x2.f32 %14, %37, %36;\nshf.l.wrap.b32 y, %2, %2, 7;\n"
        "add.u32 %2, y, %42;\nshf.l.wrap.b32 y, %7, %7, 7;\nadd.u32 %7, y, %47;\nfma.rn.f16x2 %5, %83, cm, %21;\nfma.rn.f16x2 %0, %83, cm, %16;\n"
        "fma.rn.f16x2 %3, %83, cm, %19;\nfma.rn.f16x2 %45, %5, %76, c3;\nex2.approx.ftz.f32 %26, %26;\n"
        "L2_6:\nex2.approx.ftz.f32 %27, %27;\ncvt.rn.bf16x2.f32 %12, %33, %32;\nfma.rn.f16x2 %40, %0, %76, c3;\nfma.rn.f16x2 %1, %83, cm, %17;\n"
        "fma.rn.f16x2 %45, %21, c2, %45;\nfma.rn.f16x2 %40, %16, c2, %40;\nfma.rn.f16x2 %41, %1, %76, c3;\nex2.approx.ftz.f32 %34, %34;\n"
        "L2_7:\nex2.approx.ftz.f32 %35, %35;\nfma.rn.f16x2 %21, %45, %45, c1;\nfma.rn.f16x2 %16, %40, %40, c1;\nex2.approx.ftz.f32 %38, %38;\n"
        "fma.rn.f16x2 %40, %16, %40, c0;\nfma.rn.f16x2 %45, %21, %45, c0;\nfma.rn.f16x2 %41, %17, c2, %41;\nshf.l.wrap.b32 y, %0, %0, 7;\nadd.u32 %0, y, %40;\n"
        "cvt.rn.bf16x2.f32 %13, %35, %34;\n"
        "L2_8:\nshf.l.wrap.b32 y, %5, %5, 7;\nadd.u32 %5, y, %45;\nfma.rn.f16x2 %6, %83, cm, %22;\nex2.approx.ftz.f32 %39, %39;\n"
        "cvt.rn.bf16x2.f32 %9, %27, %26;\n"
        "L2_9:\nfma.rn.f16x2 %43, %3, %76, c3;\nfma.rn.f16x2 %17, %41, %41, c1;\nex2.approx.ftz.f32 %24, %24;\nex2.approx.ftz.f32 %25, %25;\n"
        "L2_10:\nfma.rn.f16x2 %41, %17, %41, c0;\nfma.rn.f16x2 %43, %19, c2, %43;\n"
        "L2_11:\nfma.rn.f16x2 %46, %6, %76, c3;\nshf.l.wrap.b32 y, %1, %1, 7;\nadd.u32 %1, y, %41;\ncvt.rn.bf16x2.f32 %15, %39, %38;\n"
        "ex2.approx.ftz.f32 %30, %30;\n"
        "L2_12:\nfma.rn.f16x2 %19, %43, %43, c1;\n"
        "L2_13:\nfma.rn.f16x2 %46, %22, c2, %46;\ncvt.rn.bf16x2.f32 %8, %25, %24;\nex2.approx.ftz.f32 %31, %31;\nfma.rn.f16x2 %22, %46, %46, c1;\n"
        "L2_14:\nfma.rn.f16x2 %46, %22, %46, c0;\n"
        "L2_15:\nfma.rn.f16x2 %43, %19, %43, c0;\nshf.l.wrap.b32 y, %3, %3, 7;\nadd.u32 %3, y, %43;\nshf.l.wrap.b32 y, %6, %6, 7;\nadd.u32 %6, y, %46;\n"
        "mov.b64 dv, {v, h1};\nadd.s64 d7, dv, -46136640;\nwgmma.fence.sync.aligned;\n"
        "wgmma.mma_async.sync.aligned.m64n40k16.f32.bf16.bf16 {%48, %49, %50, %51, %52, %53, %54, %55, %56, %57, %58, %59, %60, %61, %62, %63, %64, %65, %66, %67}, {%12, %13, %14, %15}, d7, pt, 1, 1, 1;\n"
        "L2_16:\ncvt.rn.bf16x2.f32 %11, %31, %30;\nmov.b64 dv, {v, h1};\nadd.s64 d2, dv, -384;\nadd.s64 d5, dv, -37748160;\nadd.s64 d6, dv, -41942400;\n"
        "add.s64 d3, dv, -382;\nadd.s64 d0, dv, -512;\nadd.s64 d1, dv, -510;\nadd.s64 d4, dv, -33553920;\nwgmma.fence.sync.aligned;\n"
        "wgmma.mma_async.sync.aligned.m64n32k16.f32.f16.f16 {%24, %25, %26, %27, %28, %29, %30, %31, %32, %33, %34, %35, %36, %37, %38, %39}, {%68, %69, %70, %71}, d2, pf, 1, 1, 0;\n"
        "wgmma.mma_async.sync.aligned.m64n40k16.f32.bf16.bf16 {%48, %49, %50, %51, %52, %53, %54, %55, %56, %57, %58, %59, %60, %61, %62, %63, %64, %65, %66, %67}, {%4, %5, %6, %7}, d5, pt, 1, 1, 1;\n"
        "wgmma.mma_async.sync.aligned.m64n40k16.f32.bf16.bf16 {%48, %49, %50, %51, %52, %53, %54, %55, %56, %57, %58, %59, %60, %61, %62, %63, %64, %65, %66, %67}, {%8, %9, %10, %11}, d6, pt, 1, 1, 1;\n"
        "wgmma.mma_async.sync.aligned.m64n32k16.f32.f16.f16 {%24, %25, %26, %27, %28, %29, %30, %31, %32, %33, %34, %35, %36, %37, %38, %39}, {%72, %73, %74, %75}, d3, pt, 1, 1, 0;\n"
        "wgmma.mma_async.sync.aligned.m64n32k16.f16.f16.f16 {%16, %17, %18, %19, %20, %21, %22, %23}, {%68, %69, %70, %71}, d0, pf, 1, 1, 0;\n"
        "wgmma.mma_async.sync.aligned.m64n32k16.f16.f16.f16 {%16, %17, %18, %19, %20, %21, %22, %23}, {%72, %73, %74, %75}, d1, pt, 1, 1, 0;\n"
        "wgmma.mma_async.sync.aligned.m64n40k16.f32.bf16.bf16 {%48, %49, %50, %51, %52, %53, %54, %55, %56, %57, %58, %59, %60, %61, %62, %63, %64, %65, %66, %67}, {%0, %1, %2, %3}, d4, pt, 1, 1, 1;\n"
        "wgmma.commit_group.sync.aligned;\n@pl bra.uni NOQ;\nwgmma.wait_group.sync.aligned 0;\nxor.b32 y, %82, 0;\nld.shared.u32 %68, [y];\n"
        "ld.shared.u32 %69, [y+512];\nxor.b32 y, %82, 16;\nld.shared.u32 %70, [y];\nld.shared.u32 %71, [y+512];\nxor.b32 y, %82, 32;\nld.shared.u32 %72, [y];\n"
        "ld.shared.u32 %73, [y+512];\nxor.b32 y, %82, 48;\nld.shared.u32 %74, [y];\nld.shared.u32 %75, [y+512];\nshl.b32 y, %68, 16;\n"
        "and.b32 %68, %68, 0xFFFF0000;\ncvt.rn.f16x2.f32 %68, %68, y;\nshl.b32 y, %69, 16;\nand.b32 %69, %69, 0xFFFF0000;\ncvt.rn.f16x2.f32 %69, %69, y;\n"
        "shl.b32 y, %70, 16;\nand.b32 %70, %70, 0xFFFF0000;\ncvt.rn.f16x2.f32 %70, %70, y;\nshl.b32 y, %71, 16;\nand.b32 %71, %71, 0xFFFF0000;\n"
        "cvt.rn.f16x2.f32 %71, %71, y;\nshl.b32 y, %72, 16;\nand.b32 %72, %72, 0xFFFF0000;\ncvt.rn.f16x2.f32 %72, %72, y;\nshl.b32 y, %73, 16;\n"
        "and.b32 %73, %73, 0xFFFF0000;\ncvt.rn.f16x2.f32 %73, %73, y;\nshl.b32 y, %74, 16;\nand.b32 %74, %74, 0xFFFF0000;\ncvt.rn.f16x2.f32 %74, %74, y;\n"
        "shl.b32 y, %75, 16;\nand.b32 %75, %75, 0xFFFF0000;\ncvt.rn.f16x2.f32 %75, %75, y;\n"
        "NOQ:\nwgmma.wait_group.sync.aligned 0;\nfma.rn.f16x2 %7, %83, cm, %23;\nex2.approx.ftz.f32 %28, %28;\nfma.rn.f16x2 %47, %7, %76, c3;\n"
        "fma.rn.f16x2 %4, %83, cm, %20;\nfma.rn.f16x2 %2, %83, cm, %18;\nfma.rn.f16x2 %44, %4, %76, c3;\n"
        "L3_1:\nfma.rn.f16x2 %44, %20, c2, %44;\nex2.approx.ftz.f32 %29, %29;\nfma.rn.f16x2 %47, %23, c2, %47;\nfma.rn.f16x2 %42, %2, %76, c3;\n"
        "L3_2:\nex2.approx.ftz.f32 %36, %36;\nfma.rn.f16x2 %23, %47, %47, c1;\nfma.rn.f16x2 %20, %44, %44, c1;\n"
        "L3_3:\nfma.rn.f16x2 %42, %18, c2, %42;\nfma.rn.f16x2 %44, %20, %44, c0;\nex2.approx.ftz.f32 %37, %37;\ncvt.rn.bf16x2.f32 %10, %29, %28;\n"
        "L3_4:\nfma.rn.f16x2 %18, %42, %42, c1;\nex2.approx.ftz.f32 %32, %32;\nfma.rn.f16x2 %47, %23, %47, c0;\nshf.l.wrap.b32 y, %4, %4, 7;\n"
        "add.u32 %4, y, %44;\n"
        "L3_5:\nfma.rn.f16x2 %42, %18, %42, c0;\nex2.approx.ftz.f32 %33, %33;\ncvt.rn.bf16x2.f32 %14, %37, %36;\nshf.l.wrap.b32 y, %2, %2, 7;\n"
        "add.u32 %2, y, %42;\nshf.l.wrap.b32 y, %7, %7, 7;\nadd.u32 %7, y, %47;\nfma.rn.f16x2 %5, %83, cm, %21;\nfma.rn.f16x2 %0, %83, cm, %16;\n"
        "fma.rn.f16x2 %3, %83, cm, %19;\nfma.rn.f16x2 %45, %5, %76, c3;\nex2.approx.ftz.f32 %26, %26;\n"
        "L3_6:\nex2.approx.ftz.f32 %27, %27;\ncvt.rn.bf16x2.f32 %12, %33, %32;\nfma.rn.f16x2 %40, %0, %76, c3;\nfma.rn.f16x2 %1, %83, cm, %17;\n"
        "fma.rn.f16x2 %45, %21, c2, %45;\nfma.rn.f16x2 %40, %16, c2, %40;\nfma.rn.f16x2 %41, %1, %76, c3;\nex2.approx.ftz.f32 %34, %34;\n"
        "L3_7:\nex2.approx.ftz.f32 %35, %35;\nfma.rn.f16x2 %21, %45, %45, c1;\nfma.rn.f16x2 %16, %40, %40, c1;\nex2.approx.ftz.f32 %38, %38;\n"
        "fma.rn.f16x2 %40, %16, %40, c0;\nfma.rn.f16x2 %45, %21, %45, c0;\nfma.rn.f16x2 %41, %17, c2, %41;\nshf.l.wrap.b32 y, %0, %0, 7;\nadd.u32 %0, y, %40;\n"
        "cvt.rn.bf16x2.f32 %13, %35, %34;\n"
        "L3_8:\nshf.l.wrap.b32 y, %5, %5, 7;\nadd.u32 %5, y, %45;\nfma.rn.f16x2 %6, %83, cm, %22;\nex2.approx.ftz.f32 %39, %39;\n"
        "cvt.rn.bf16x2.f32 %9, %27, %26;\n"
        "L3_9:\nfma.rn.f16x2 %43, %3, %76, c3;\nfma.rn.f16x2 %17, %41, %41, c1;\nex2.approx.ftz.f32 %24, %24;\nex2.approx.ftz.f32 %25, %25;\n"
        "L3_10:\nfma.rn.f16x2 %41, %17, %41, c0;\nfma.rn.f16x2 %43, %19, c2, %43;\n"
        "L3_11:\nfma.rn.f16x2 %46, %6, %76, c3;\nshf.l.wrap.b32 y, %1, %1, 7;\nadd.u32 %1, y, %41;\ncvt.rn.bf16x2.f32 %15, %39, %38;\n"
        "ex2.approx.ftz.f32 %30, %30;\n"
        "L3_12:\nfma.rn.f16x2 %19, %43, %43, c1;\n"
        "L3_13:\nfma.rn.f16x2 %46, %22, c2, %46;\ncvt.rn.bf16x2.f32 %8, %25, %24;\nex2.approx.ftz.f32 %31, %31;\nfma.rn.f16x2 %22, %46, %46, c1;\n"
        "L3_14:\nfma.rn.f16x2 %46, %22, %46, c0;\n"
        "L3_15:\nfma.rn.f16x2 %43, %19, %43, c0;\nshf.l.wrap.b32 y, %3, %3, 7;\nadd.u32 %3, y, %43;\nshf.l.wrap.b32 y, %6, %6, 7;\nadd.u32 %6, y, %46;\n"
        "mov.b64 dv, {v, h1};\nadd.s64 d7, dv, -62913600;\nwgmma.fence.sync.aligned;\n"
        "wgmma.mma_async.sync.aligned.m64n40k16.f32.bf16.bf16 {%48, %49, %50, %51, %52, %53, %54, %55, %56, %57, %58, %59, %60, %61, %62, %63, %64, %65, %66, %67}, {%12, %13, %14, %15}, d7, pt, 1, 1, 1;\n"
        "L3_16:\ncvt.rn.bf16x2.f32 %11, %31, %30;\nmov.b64 dv, {v, h1};\nadd.s64 d2, dv, -128;\nadd.s64 d5, dv, -54525120;\nadd.s64 d6, dv, -58719360;\n"
        "add.s64 d3, dv, -126;\nadd.s64 d0, dv, -256;\nadd.s64 d1, dv, -254;\nadd.s64 d4, dv, -50330880;\nwgmma.fence.sync.aligned;\n"
        "wgmma.mma_async.sync.aligned.m64n32k16.f32.f16.f16 {%24, %25, %26, %27, %28, %29, %30, %31, %32, %33, %34, %35, %36, %37, %38, %39}, {%68, %69, %70, %71}, d2, pf, 1, 1, 0;\n"
        "wgmma.mma_async.sync.aligned.m64n40k16.f32.bf16.bf16 {%48, %49, %50, %51, %52, %53, %54, %55, %56, %57, %58, %59, %60, %61, %62, %63, %64, %65, %66, %67}, {%4, %5, %6, %7}, d5, pt, 1, 1, 1;\n"
        "wgmma.mma_async.sync.aligned.m64n40k16.f32.bf16.bf16 {%48, %49, %50, %51, %52, %53, %54, %55, %56, %57, %58, %59, %60, %61, %62, %63, %64, %65, %66, %67}, {%8, %9, %10, %11}, d6, pt, 1, 1, 1;\n"
        "wgmma.mma_async.sync.aligned.m64n32k16.f32.f16.f16 {%24, %25, %26, %27, %28, %29, %30, %31, %32, %33, %34, %35, %36, %37, %38, %39}, {%72, %73, %74, %75}, d3, pt, 1, 1, 0;\n"
        "wgmma.mma_async.sync.aligned.m64n32k16.f16.f16.f16 {%16, %17, %18, %19, %20, %21, %22, %23}, {%68, %69, %70, %71}, d0, pf, 1, 1, 0;\n"
        "wgmma.mma_async.sync.aligned.m64n32k16.f16.f16.f16 {%16, %17, %18, %19, %20, %21, %22, %23}, {%72, %73, %74, %75}, d1, pt, 1, 1, 0;\n"
        "wgmma.mma_async.sync.aligned.m64n40k16.f32.bf16.bf16 {%48, %49, %50, %51, %52, %53, %54, %55, %56, %57, %58, %59, %60, %61, %62, %63, %64, %65, %66, %67}, {%0, %1, %2, %3}, d4, pt, 1, 1, 1;\n"
        "wgmma.commit_group.sync.aligned;\n@pl bra.uni LOOP;\nbra.uni END;\n"
        "SLOW:\nmov.u32 cnt, 0;\n"
        "SPIN:\nmbarrier.try_wait.parity.shared::cta.b64 p, [ja+-8], %79;\n@p bra.uni BACK;\nadd.u32 cnt, cnt, 1;\nsetp.lt.u32 p, cnt, 0x1000000;\n"
        "@p bra.uni SPIN;\nsetp.eq.u32 p, %81, 0;\n@p trap;\nwgmma.wait_group.sync.aligned 0;\n"
        "TBL: .branchtargets L0_1, L0_2, L0_3, L0_4, L0_5, L0_6, L0_7, L0_8, L0_9, L0_10, L0_11, L0_12, L0_13, L0_14, L0_15, L0_16, L1_1, L1_2, L1_3, L1_4, L1_5, L1_6, L1_7, L1_8, L1_9, L1_10, L1_11, L1_12, L1_13, L1_14, L1_15, L1_16, L2_1, L2_2, L2_3, L2_4, L2_5, L2_6, L2_7, L2_8, L2_9, L2_10, L2_11, L2_12, L2_13, L2_14, L2_15, L2_16, L3_1, L3_2, L3_3, L3_4, L3_5, L3_6, L3_7, L3_8, L3_9, L3_10, L3_11, L3_12, L3_13, L3_14, L3_15, L3_16;\n"
        "brx.idx.uni %81, TBL;\n"
        "END:\n}\n"
        : "+r"(P[0]), "+r"(P[1]), "+r"(P[2]), "+r"(P[3]), "+r"(P[4]), "+r"(P[5]), "+r"(P[6]), "+r"(P[7]), "+r"(P[8]), "+r"(P[9]),
          "+r"(P[10]), "+r"(P[11]), "+r"(P[12]), "+r"(P[13]), "+r"(P[14]), "+r"(P[15]),
          "+r"(S[0]), "+r"(S[1]), "+r"(S[2]), "+r"(S[3]), "+r"(S[4]), "+r"(S[5]), "+r"(S[6]), "+r"(S[7]), "+r"(S[8]), "+r"(S[9]),
          "+r"(S[10]), "+r"(S[11]), "+r"(S[12]), "+r"(S[13]), "+r"(S[14]), "+r"(S[15]), "+r"(S[16]), "+r"(S[17]), "+r"(S[18]), "+r"(S[19]),
          "+r"(S[20]), "+r"(S[21]), "+r"(S[22]), "+r"(S[23]),
          "+r"(T[0]), "+r"(T[1]), "+r"(T[2]), "+r"(T[3]), "+r"(T[4]), "+r"(T[5]), "+r"(T[6]), "+r"(T[7]),
          "+f"(O[0]), "+f"(O[1]), "+f"(O[2]), "+f"(O[3]), "+f"(O[4]), "+f"(O[5]), "+f"(O[6]), "+f"(O[7]), "+f"(O[8]), "+f"(O[9]),
          "+f"(O[10]), "+f"(O[11]), "+f"(O[12]), "+f"(O[13]), "+f"(O[14]), "+f"(O[15]), "+f"(O[16]), "+f"(O[17]), "+f"(O[18]), "+f"(O[19]),
          "+r"(Q[0]), "+r"(Q[1]), "+r"(Q[2]), "+r"(Q[3]), "+r"(Q[4]), "+r"(Q[5]), "+r"(Q[6]), "+r"(Q[7])
        : "r"(c_al), "r"(v0), "r"(ja0), "r"(par), "r"(rel), "r"(never), "r"(qa), "r"(c_m) : "memory");
}
__device__ __forceinline__ void attn_qk(uint32_t (&S)[NS], const uint32_t (&Q)[8], uint64_t d) {
    asm volatile("{\n.reg .pred pt, pf;\n.reg .b64 d<3>;\nsetp.eq.u32 pt, 0, 0;\nsetp.ne.u32 pf, 0, 0;\nadd.s64 d0, %32, 2;\nadd.s64 d1, %32, 128;\nadd.s64 d2, %32, 130;\n"
        "wgmma.mma_async.sync.aligned.m64n32k16.f16.f16.f16 {%0, %1, %2, %3, %4, %5, %6, %7}, {%24, %25, %26, %27}, %32, pf, 1, 1, 0;\n"
        "wgmma.mma_async.sync.aligned.m64n32k16.f16.f16.f16 {%0, %1, %2, %3, %4, %5, %6, %7}, {%28, %29, %30, %31}, d0, pt, 1, 1, 0;\n"
        "wgmma.mma_async.sync.aligned.m64n32k16.f32.f16.f16 {%8, %9, %10, %11, %12, %13, %14, %15, %16, %17, %18, %19, %20, %21, %22, %23}, {%24, %25, %26, %27}, d1, pf, 1, 1, 0;\n"
        "wgmma.mma_async.sync.aligned.m64n32k16.f32.f16.f16 {%8, %9, %10, %11, %12, %13, %14, %15, %16, %17, %18, %19, %20, %21, %22, %23}, {%28, %29, %30, %31}, d2, pt, 1, 1, 0;\n"
        "}\n"
        : "+r"(S[0]), "+r"(S[1]), "+r"(S[2]), "+r"(S[3]), "+r"(S[4]), "+r"(S[5]), "+r"(S[6]), "+r"(S[7]), "+r"(S[8]), "+r"(S[9]),
          "+r"(S[10]), "+r"(S[11]), "+r"(S[12]), "+r"(S[13]), "+r"(S[14]), "+r"(S[15]), "+r"(S[16]), "+r"(S[17]), "+r"(S[18]), "+r"(S[19]),
          "+r"(S[20]), "+r"(S[21]), "+r"(S[22]), "+r"(S[23])
        : "r"(Q[0]), "r"(Q[1]), "r"(Q[2]), "r"(Q[3]), "r"(Q[4]), "r"(Q[5]), "r"(Q[6]), "r"(Q[7]), "l"(d));
}
constexpr uint32_t KV_HI = (512 >> 4) | (2u << 30);
constexpr int VINC = 1 - 65536;
__device__ __forceinline__ uint64_t kvdesc(uint32_t lo) { return ((uint64_t)KV_HI << 32) | lo; }
__device__ __forceinline__ void attn_qk(uint32_t (&S)[32], const uint32_t (&Qf)[8], uint64_t d) {
    wgmma_ru_n64_t0(S, Qf[0], Qf[1], Qf[2], Qf[3], d, 0);
    wgmma_ru_n64_t0(S, Qf[4], Qf[5], Qf[6], Qf[7], d + 2, 1);
}
__device__ __forceinline__ uint32_t bf2h(uint32_t v) {
    uint32_t r; asm("cvt.rn.f16x2.f32 %0, %1, %2;" : "=r"(r) : "f"(__uint_as_float(v & 0xFFFF0000u)), "f"(__uint_as_float(v << 16))); return r;
}
__device__ __forceinline__ uint4 bf2h(uint4 v) { return make_uint4(bf2h(v.x), bf2h(v.y), bf2h(v.z), bf2h(v.w)); }
__device__ __forceinline__ void attn_loadq(uint32_t (&Qf)[8], uint32_t qa) {
#pragma unroll
    for (int j = 0; j < 4; j++) {
        Qf[(j >> 1) * 4 + (j & 1) * 2] = lds32(qa ^ (j << 4));
        Qf[(j >> 1) * 4 + (j & 1) * 2 + 1] = lds32((qa ^ (j << 4)) + 512);
    }
}

template <bool FAST, int NSX>
__device__ __forceinline__ int attn_rounds(uint32_t (&S)[NSX], uint32_t (&Qf)[8], uint32_t sb, uint32_t qa, uint32_t rel, uint32_t ooff, uint32_t c_al,
                                           int r, int lane, uint32_t zero) {
    uint32_t P[16], T[NP] = {};
    float Oa[20];
    const uint32_t vd0 = (((sb & 0x3FFFF) + 32768) >> 4) | (((OFF_ONES - 32768) >> 4) << 16);
    const uint32_t kd0 = vd0 - 1024;
    const uint32_t kdn = kd0 + 3 * (SLOT / 16) + 768;
#pragma unroll
    for (int i = 0; i < 16; i++) P[i] = 0;
    pin(P); pin(T);
    const uint32_t c_m = c_al ^ (0xa1c0a1c0u ^ 0x50a050a0u);
    if constexpr (!FAST) {
        ooff += (r >> 1) * (SEQ * 128);
        attn_loadq(Qf, qa);
        pin(Qf);
        wg_fence();
        attn_qk(S, Qf, kvdesc(r ? kdn : kd0 - (16384 - OFF_K0) / 16));
        wg_commit();
    }
    int rend = 4;
#pragma unroll 1
    do {
        wg_wait<0>();
#pragma unroll
        for (int i = 0; i < 20; i++) Oa[i] = 0.f;
        pin(Oa);
        if constexpr (FAST) {
            attn_round_asm(S, P, T, Oa, Qf, c_al, vd0, sb + OFF_BAR + B_AF, r & 1, rel, zero, qa, c_m);
        } else {
            float m0 = -INFINITY, m1 = -INFINITY;
#pragma unroll 1
            for (int u = 0; u < 32; u++) {
                const uint32_t off = ((u >> 2) & 3) * (SLOT / 16) + (u & 3) * 256;
                if ((u & 3) == 0) mbar_wait(sb + OFF_BAR + B_AF + 2 * u, r & 1);
                wg_wait<0>();
                pin(S); pin(Oa);
                if ((u & 3) == 0 && rel) mbar_arrive_cluster(sb + OFF_BAR + B_AF + 2 * u + rel);
                float n0 = m0, n1 = m1;
#pragma unroll
                for (int e = 0; e < 8; e++) {
                    n0 = fmaxf(n0, fmaxf(__uint_as_float(S[4 * e]), __uint_as_float(S[4 * e + 1])));
                    n1 = fmaxf(n1, fmaxf(__uint_as_float(S[4 * e + 2]), __uint_as_float(S[4 * e + 3])));
                }
                n0 = fmaxf(n0, shx(n0, 1)); n1 = fmaxf(n1, shx(n1, 1));
                n0 = fmaxf(n0, shx(n0, 2)); n1 = fmaxf(n1, shx(n1, 2));
                const float b0 = (n0 == -INFINITY) ? 0.f : n0, b1 = (n1 == -INFINITY) ? 0.f : n1;
                const float a0 = ex2f(m0 - b0), a1 = ex2f(m1 - b1);
                m0 = n0; m1 = n1;
#pragma unroll
                for (int e = 0; e < 5; e++) { Oa[4 * e] *= a0; Oa[4 * e + 1] *= a0; Oa[4 * e + 2] *= a1; Oa[4 * e + 3] *= a1; }
#pragma unroll
                for (int e = 0; e < 16; e++) {
                    const float b = (e & 1) ? b1 : b0;
                    P[e] = pack_bf16(ex2f(__uint_as_float(S[2 * e]) - b), ex2f(__uint_as_float(S[2 * e + 1]) - b));
                }
                pin(Oa); pin(P);
                wg_fence();
                attn_qk(S, Qf, kvdesc(kd0 + off));
#pragma unroll
                for (int k = 0; k < 4; k++)
                    wgmma_rs_n40_t1(Oa, P[4 * k], P[4 * k + 1], P[4 * k + 2], P[4 * k + 3], kvdesc(vd0 + (off + k * 64) * (uint32_t)VINC), 1);
                wg_commit();
            }
        }
        if (FAST && r == 1) {
            mbar_wait(sb + OFF_BAR + B_DEP + 8, 0);
            if (!__all_sync(0xffffffffu, lds32(sb + OFF_BAR + B_FLAG + 4))) rend = 2;
        }
        wg_wait<0>();
        pin(Oa); pin(S);
        if constexpr (!FAST) {
            attn_loadq(Qf, qa);
            pin(Qf);
            wg_fence();
            attn_qk(S, Qf, kvdesc(kdn));
            wg_commit();
        }
        const float r0 = rcpf(Oa[16]), r1 = rcpf(Oa[18]);
        uint4* o = g_O + ooff;
        ooff += (r & 1) ? SEQ * 128 - 64 : 64;
        o[0] = make_uint4(pack_bf16(Oa[0] * r0, Oa[1] * r0), pack_bf16(Oa[4] * r0, Oa[5] * r0), pack_bf16(Oa[8] * r0, Oa[9] * r0), pack_bf16(Oa[12] * r0, Oa[13] * r0));
        o[8 * 128] = make_uint4(pack_bf16(Oa[2] * r1, Oa[3] * r1), pack_bf16(Oa[6] * r1, Oa[7] * r1), pack_bf16(Oa[10] * r1, Oa[11] * r1), pack_bf16(Oa[14] * r1, Oa[15] * r1));
        __syncwarp();
        if (lane == 0) mbar_arrive(sb + OFF_BAR + B_SIG);
    } while (++r < rend);
    wg_wait<0>();
    pin(S);
    return r;
}

struct Maps { CUtensorMap XA, XB, Wq, Wqkv, Wk, Wv, O, WoA, WoB, Out; };

__global__ void __cluster_dims__(2, 1, 1) __launch_bounds__(640, 1) mega_kernel(const __grid_constant__ Maps mp, const uint32_t zero) {
    extern __shared__ uint8_t smem_raw[];
    const uint32_t sb = (smem_u32(smem_raw) + 1023) & ~1023u;
    const uint32_t bars = sb + OFF_BAR;
    const int tid = threadIdx.x, lane = tid & 31;
    const int wid = __shfl_sync(0xffffffffu, tid >> 5, 0), wg = wid >> 2;
    const int cid = blockIdx.x >> 1, rank = blockIdx.x & 1;
    const bool small = cid >= 64;
    const int mblk = 2 * (cid & 7) + rank, nb = (cid >> 3) & 3;
    const int hd = cid >> 2, rb = 2 * (cid & 3) + rank;
    if (wid == 16) {
        if (lane == 0) {
            prefetch_tmap(cid < 32 || small ? &mp.XA : &mp.XB);
            prefetch_tmap(small ? &mp.Wk : (cid < 32 ? &mp.Wq : &mp.Wqkv));
            for (int s = 0; s < 4; s++) { mbar_init(bars + 16 * s, 1); mbar_init(bars + 16 * s + 8, small ? 16 : 32); }
            for (int s = 0; s < 8; s++) { mbar_init(bars + B_AF + 8 * s, 1); mbar_init(bars + B_AE + 8 * s, 32); }
            mbar_init(bars + B_SIG, 16); mbar_init(bars + B_DEP, 1); mbar_init(bars + B_DEP + 8, 1); mbar_init(bars + B_DEP + 16, 1);
            asm volatile("fence.mbarrier_init.release.cluster;" ::: "memory");
        }
        __syncwarp();
        asm volatile("barrier.cluster.arrive.relaxed.aligned;" ::: "memory");
        if (lane == 0 && !small) {
            mbar_expect_tx(bars, SLOT);
            tma_ld(sb, cid < 32 ? &mp.XA : &mp.XB, 0, mblk * 128, bars);
        }
        __syncwarp();
    } else {
        if (tid >= 256 && tid < 320) { sts128(sb + OFF_ONES + (tid - 256) * 16, make_uint4(0x3F80u, 0x3F80u, 0x3F80u, 0x3F80u)); fence_async_smem(); }
        asm volatile("barrier.cluster.arrive.relaxed.aligned;" ::: "memory");
    }
    __syncthreads();
    asm volatile("barrier.cluster.wait.aligned;" ::: "memory");

    if (wg == 4) {
        reg_dec<32>();
        if (wid == 16) {
            if (lane == 0) {
                if (small) {
                    const int r0 = (blockIdx.x - 128) * 512;
                    for (int n = 0; n < 32; n++) {
                        const uint32_t fb = bars + 16 * (n & 3), st = sb + (n & 3) * SLOT;
                        const int k0 = (n & 15) * 64, r = r0 + (n >> 4) * 256;
                        mbar_wait(fb + 8, ((n >> 2) & 1) ^ 1);
                        mbar_expect_tx(fb, 40960);
                        tma_ld(st, &mp.XA, k0, r, fb);
                        tma_ld(st + 16384, &mp.XA, k0, r + 128, fb);
                        tma_ld(st + 32768, &mp.Wk, 0, k0, fb);
                        tma_ld(st + 36864, &mp.Wv, 0, k0, fb);
                    }
                } else {
                    for (int n = 0; n < 32; n++) {
                        const uint32_t fb = bars + 16 * (n & 3), st = sb + (n & 3) * SLOT;
                        const bool isA = (n < 16 && cid < 32);
                        const int k0 = (n & 15) * 64, n0 = (n < 16 ? nb : (cid < 32 ? 4 + nb : 8 + nb)) * 256 + rank * 128;
                        if (n > 0) {
                            mbar_wait(fb + 8, ((n >> 2) & 1) ^ 1);
                            mbar_expect_tx(fb, SLOT);
                            tma_ld(st, isA ? &mp.XA : &mp.XB, k0, mblk * 128, fb);
                        }
                        tma_ld_mc(st + 16384 + rank * 16384, isA ? &mp.Wq : &mp.Wqkv, n0, k0, fb, 3);
                        tma_ld_mc(st + 24576 + rank * 16384, isA ? &mp.Wq : &mp.Wqkv, n0 + 64, k0, fb, 3);
                        if (n == 3) {
                            tma_pf(isA ? &mp.XA : &mp.XB, (4 + nb) * 64, mblk * 128);
                            tma_pf(isA ? &mp.Wq : &mp.Wqkv, n0 + (cid & 1) * 64, (4 + ((cid >> 1) & 3)) * 64);
                        }
                    }
                    const uint4 *kcur = g_Kh, *knext = g_Kh;
                    for (int n = 0; n < 32; n++) {
                        const int r = n >> 3, j = n & 7;
                        const uint32_t fb = bars + B_AF + 8 * j, st = sb + (n & 3) * SLOT;
                        if (n == 0 || n == 15 || n == 23) {
                            mbar_wait(bars + B_DEP + (n & 24), 0);
                            fence_async();
                            if (n < 16 && !lds32(bars + B_FLAG + (n & 4))) knext = g_K;
                        }
                        if (j == 0) kcur = knext;
                        const size_t kv = (size_t)(r < 2 ? 0 : (r - 2) * 16 + hd + 1) * SEQ + j * 256;
                        const int rq = n ? r + 1 : 0;
                        const bool extra = n == 0 || (j == 7 && r < 3);
                        if (n < 3) mbar_wait(bars + 16 * n + 8, 1);
                        else mbar_wait_idle(bars + B_AE + 8 * ((n - 3) & 7), ((n - 3) >> 3) & 1);
                        mbar_expect_tx(fb, (j == 7 ? 28672 : 32768) + (extra ? 20480 : 0));
                        if (extra) {
                            bulk_g2s(n ? st + 28672 : sb + OFF_K0, knext + (size_t)(rq < 2 ? 0 : (rq - 2) * 16 + hd + 1) * SEQ * 4, 4096, fb);
                            bulk_g2s(sb + OFF_Q, g_Q + ((size_t)(rq * 16 + hd) * SEQ + rb * 256) * 4, 16384, fb);
                        }
                        if (rank) bulk_g2s_mc(st + 32768, g_V + kv * 4, 16384, fb, 3);
                        else bulk_g2s_mc(st + 16384, kcur + (kv + 64) * 4, j == 7 ? 12288 : 16384, fb, 3);
                    }
                    const uint32_t target = lds32(bars + B_EPOCH) * 16;
                    const int br = cid >> 5;
                    for (int n = 0; n < 16; n++) {
                        const uint32_t fb = bars + 16 * (n & 3), st = sb + (n & 3) * SLOT;
                        if (n < 3) mbar_wait_idle(bars + B_AE + 8 * (5 + n), 1);
                        else mbar_wait(fb + 8, ((n >> 2) & 1) ^ 1);
                        mbar_expect_tx(fb, SLOT);
                        tma_ld_mc(st + 16384 + rank * 16384, br ? &mp.WoB : &mp.WoA, nb * 256 + rank * 128, n * 64, fb, 3);
                        tma_ld_mc(st + 24576 + rank * 16384, br ? &mp.WoB : &mp.WoA, nb * 256 + rank * 128 + 64, n * 64, fb, 3);
                        if ((n & 7) == 0) { cnt_wait(2 + (2 * br + (n >> 3)) * 8 + (cid & 7), target); fence_async(); }
                        tma_ld(st, &mp.O, n * 64, br * SEQ + mblk * 128, fb);
                    }
                }
            }
        } else if (wid == 17) {
            mbar_wait_idle(bars + B_SIG, 0);
            if (lane == 0) cnt_signal(0);
            mbar_wait_idle(bars + B_SIG, 1);
            if (small) {
                if (lane == 0) cnt_signal(0);
                for (int i = 0; i < 2; i++) {
                    mbar_wait_idle(bars + B_SIG, i);
                    if (lane == 0) cnt_signal(34 + i);
                }
            } else {
                if (lane < 16) {
                    const int w = lane >> 2, h = lane & 3;
                    uint4* dst = (cid < 32 ? g_K : g_V) + (size_t)SEQ * 4 + ((size_t)(nb * 8 + (w & 1) * 4 + h) * SEQ + mblk * 128 + (w >> 1) * 64) * 4;
                    bulk_s2g(dst, stage_addr(sb, w, h >> 1) + (h & 1) * 4096, 4096);
                    asm volatile("cp.async.bulk.commit_group;\ncp.async.bulk.wait_group 0;" ::: "memory");
                    fence_async();
                }
                __syncwarp();
                if (lane == 0) cnt_signal(1);
                for (int r = 0; r < 4; r++) {
                    mbar_wait_idle(bars + B_SIG, r & 1);
                    if (lane == 0) cnt_signal(2 + r * 8 + rb);
                }
            }
        } else if (wid == 18) {
            if (lane == 0) { prefetch_tmap(&mp.XB); prefetch_tmap(&mp.Wqkv); prefetch_tmap(&mp.O); prefetch_tmap(cid < 32 ? &mp.WoA : &mp.WoB); prefetch_tmap(&mp.Out); }
            const uint32_t ep = __ldcg(g_epoch + blockIdx.x) + 1;
            __syncwarp();
            if (lane == 0) { g_epoch[blockIdx.x] = ep; sts32(bars + B_EPOCH, ep); }
            if (small) {
                cnt_wait(1, ep * 128);
                if (lane == 0) mbar_arrive(bars + B_DEP);
            } else for (int half = 0; half < 3; half++) {
                if (half) cnt_wait(33 + half, ep * 4, 500);
                else cnt_wait(0, ep * 136);
                if (half == 2) { if (lane == 0) mbar_arrive(bars + B_DEP + 16); break; }
                bool safe = true;
                for (int r = 2 * half; r < 2 * half + 2; r++) {
                    const int bh = r * 16 + hd, kvh = half ? bh - 31 : 0;
                    const uint32_t q = __ldcg((const uint32_t*)g_nrm + bh * 128 + (rb >> 1) * 32 + lane);
                    const uint4 k = __ldcg((const uint4*)(g_nrm + (64 + kvh) * 128) + lane);
                    const uint4 v = __ldcg((const uint4*)(g_nrm + (97 + kvh) * 128) + lane);
                    const float qm = __uint_as_float(__reduce_max_sync(0xffffffffu, q));
                    const float km = __uint_as_float(__reduce_max_sync(0xffffffffu, max(max(k.x, k.y), max(k.z, k.w))));
                    const float vm = __uint_as_float(__reduce_max_sync(0xffffffffu, max(max(v.x, v.y), max(v.z, v.w))));
                    safe = safe && (qm * km <= 3600.0f) && (qm <= 1.0e6f) && (km <= 1.0e6f) && (vm <= 1.0e24f) && (vm >= 1.0e-24f);
                }
                if (lane == 0) { sts32(bars + B_FLAG + 4 * half, safe); mbar_arrive(bars + B_DEP + 8 * half); }
            }
        }
    } else {
        reg_inc<112>();
        const int warp = wid & 3, g = lane >> 2, c = lane & 3;
        if (small) {
            float acc[32];
#pragma unroll 1
            for (int n = 0; n < 32; n++) {
                const int s = n & 3;
                mbar_wait(bars + 16 * s, (n >> 2) & 1);
                const uint64_t da = mkdesc(sb + s * SLOT + wg * 8192, 16, 1024, 1);
                const uint64_t db = mkdesc(sb + s * SLOT + 32768, 4096, 512, 2);
                wg_fence();
#pragma unroll
                for (int k = 0; k < 4; k++) wgmma_ss_n64_t1(acc, da + 2 * k, db + 64 * k, (k > 0) ? 1 : (n & 15));
                wg_commit();
                wg_wait<0>();
                pin(acc);
                if (lane == 0) mbar_arrive(bars + 16 * s + 8);
                if ((n & 15) == 15) {
                    const int row = (blockIdx.x - 128) * 512 + (n >> 4) * 256 + wg * 64 + warp * 16 + g;
                    const int off = row * 4 + (c ^ ((row >> 1) & 3));
#pragma unroll
                    for (int h = 0; h < 2; h++) {
                        const float* v = &acc[16 * h];
                        uint4* dst = (h == 0 ? g_K : g_V) + off;
                        const uint4 w0 = make_uint4(pack_bf16(v[0], v[1]), pack_bf16(v[4], v[5]), pack_bf16(v[8], v[9]), pack_bf16(v[12], v[13]));
                        const uint4 w1 = make_uint4(pack_bf16(v[2], v[3]), pack_bf16(v[6], v[7]), pack_bf16(v[10], v[11]), pack_bf16(v[14], v[15]));
                        dst[0] = w0;
                        dst[32] = w1;
                        if (h == 0) { g_Kh[off] = bf2h(w0); g_Kh[off + 32] = bf2h(w1); }
                        float a = 0.f, b = 0.f;
#pragma unroll
                        for (int j = 0; j < 4; j++) {
                            a = fmaf(v[4 * j], v[4 * j], fmaf(v[4 * j + 1], v[4 * j + 1], a));
                            b = fmaf(v[4 * j + 2], v[4 * j + 2], fmaf(v[4 * j + 3], v[4 * j + 3], b));
                        }
                        a += shx(a, 1); b += shx(b, 1);
                        a += shx(a, 2); b += shx(b, 2);
                        const uint32_t u = __reduce_max_sync(0xffffffffu, max(__float_as_uint(a), __float_as_uint(b)));
                        if (lane == 0) g_nrm[(h == 0 ? 64 : 97) * 128 + (row >> 4)] = __uint_as_float(u);
                    }
                    __syncwarp();
                    if (lane == 0) mbar_arrive(bars + B_SIG);
                }
            }
            mbar_wait_idle(bars + B_DEP, 0);
#pragma unroll 1
            for (int i = 0; i < 8; i++) {
                const int o = SEQ * 4 * (1 + (i >> 2) * 16 + (blockIdx.x - 128) * 4 + (i & 3)) + tid;
                uint4 w[16];
#pragma unroll
                for (int k = 0; k < 16; k++) w[k] = __ldcg(g_K + o + k * 512);
#pragma unroll
                for (int k = 0; k < 16; k++) g_Kh[o + k * 512] = bf2h(w[k]);
                if ((i & 3) == 3) {
                    bar_sync(8, 512);
                    if (lane == 0) mbar_arrive(bars + B_SIG);
                }
            }
        } else {
            const int mh = wg >> 1, nh = wg & 1;
            const uint32_t relbar = lane < 2 ? mapa(bars + 8, lane) : 0;
            const uint32_t da0 = __shfl_sync(0xffffffffu, (uint32_t)mkdesc(sb + (tid >> 8) * 8192, 16, 1024, 1), 0);
            const uint32_t db0 = __shfl_sync(0xffffffffu, (uint32_t)mkdesc(sb + 16384 + ((tid >> 7) & 1) * 16384, 8192, 1024, 1), 0);
            const int rloc = warp * 16 + g;
            const int csw = c ^ ((g >> 1) & 3);
            {
                float acc[64];
                uint4 pk[8];
                float ss[8] = {};
                const int row = mblk * 128 + mh * 64 + rloc, h0 = nb * 8 + nh * 4;
#pragma unroll 1
                for (int kb = 0; kb < 15; kb++) gemm_kstep(acc, sb, da0, db0, relbar, kb, kb > 0);
                gemm_finish<1, 15>(acc, sb, da0, db0, relbar, wg);
                proj_pack<true>(acc, pk, ss);
                uint4* dst = g_Q + ((size_t)((cid & 32) + h0) * SEQ + row) * 4 + csw;
#pragma unroll
                for (int i = 0; i < 4; i++) sts128(sb + OFF_Q + i * 8192 + tid * 16, pk[4 + i]);
                gemm_kstep(acc, sb, da0, db0, relbar, 0, false);
#pragma unroll 1
                for (int kb = 0; kb < 8; kb++) {
                    dst[(kb >> 1) * SEQ * 4 + (kb & 1) * 32] = pk[0];
#pragma unroll
                    for (int i = 0; i < 7; i++) ss[i] = ss[i + 1];
                    ss[7] = sumsq(pk[0]);
                    pk[0] = pk[1]; pk[1] = pk[2]; pk[2] = pk[3];
                    pk[3] = lds128(sb + OFF_Q + (kb & 3) * 8192 + tid * 16);
                    gemm_kstep(acc, sb, da0, db0, relbar, kb + 1, true);
                }
                publish_norms(ss, g_nrm + ((cid & 32) + h0 + c) * 128 + (row >> 4), lane);
                __syncwarp();
                if (lane == 0) mbar_arrive(bars + B_SIG);
#pragma unroll 1
                for (int kb = 9; kb < 15; kb++) gemm_kstep(acc, sb, da0, db0, relbar, kb, true);
                const uint32_t c_al = __shfl_sync(0xffffffffu, 0xa1c0a1c0u + zero, lane);
                const uint32_t qa = __shfl_sync(0xffffffffu, sb + OFF_Q + (wg * 64 + rloc) * 64 + (((g >> 1) & 3) << 4) + c * 4, lane);
                const uint32_t rel = __shfl_sync(0xffffffffu, relbar ? relbar - (bars + 8) + (B_AE - B_AF) : 0, lane);
                const uint32_t ooff = __shfl_sync(0xffffffffu, (rb * 256 + wg * 64 + rloc) * 128 + hd * 4 + c, lane);
                const uint32_t noff = __shfl_sync(0xffffffffu, ((cid < 32 ? 65 : 98) + h0 + c) * 128 + (row >> 4), lane);
                const uint32_t soff = __shfl_sync(0xffffffffu, rloc * 64 + csw * 16, lane);
                mbar_wait(bars + B_DEP, 0);
                const bool fast = __all_sync(0xffffffffu, lds32(bars + B_FLAG));
                gemm_finish<1, 14>(acc, sb, da0, db0, relbar, wg);
                stage_acquire(wg);
                proj_pack<false>(acc, pk, ss);
#pragma unroll
                for (int i = 0; i < 8; i++) sts128(stage_addr(sb, wg, i >> 2) + ((i >> 1) & 1) * 4096 + (i & 1) * 512 + soff, pk[i]);
                pin(ss);
                uint32_t S[NS], Qf[8];
                mbar_wait(bars + B_AF, 0);
                attn_loadq(Qf, qa);
#pragma unroll
                for (int i = 0; i < 8; i++) Qf[i] = bf2h(Qf[i]);
                pin(Qf);
                wg_fence();
                attn_qk(S, Qf, kvdesc(((sb & 0x3FFFF) + OFF_K0) >> 4));
                wg_commit();
                fence_async_smem();
                publish_norms(ss, g_nrm + noff, lane);
                __syncwarp();
                if (lane == 0) mbar_arrive(bars + B_SIG);
                wg_wait<0>();
                pin(S);
                int r = 0;
                if (fast) r = attn_rounds<true>(S, Qf, sb, qa, rel, ooff, c_al, 0, lane, zero);
                if (r < 4) {
                    uint32_t S2[32], Q2[8];
                    attn_rounds<false>(S2, Q2, sb, qa, rel, ooff, c_al, r, lane, zero);
                }
                if (relbar) mbar_arrive_cluster(relbar + 48);
            }
            {
                float acc[64];
#pragma unroll 1
                for (int kb = 0; kb < 13; kb++) gemm_kstep(acc, sb, da0, db0, relbar, kb, kb > 0 && kb <= 12);
                gemm_finish<3, 11>(acc, sb, da0, db0, relbar, wg);
                stage_acquire(wg);
                const int row = warp * 16 + (lane & 7) + ((lane >> 3) & 1) * 8;
#pragma unroll
                for (int ch = 0; ch < 2; ch++) {
                    const uint32_t base = stage_addr(sb, wg, ch);
#pragma unroll
                    for (int jj = 0; jj < 4; jj++) {
                        const float* v = &acc[32 * ch + 8 * jj];
                        const uint32_t addr = base + row * 128 + (((2 * jj + (lane >> 4)) ^ (lane & 7)) << 4);
                        asm volatile("stmatrix.sync.aligned.m8n8.x4.shared.b16 [%0], {%1, %2, %3, %4};" ::"r"(addr), "r"(pack_bf16(v[0], v[1])), "r"(pack_bf16(v[2], v[3])),
                                     "r"(pack_bf16(v[4], v[5])), "r"(pack_bf16(v[6], v[7])) : "memory");
                    }
                    fence_async_smem();
                    __syncwarp();
                    if (lane == 0) {
                        tma_st(&mp.Out, base + warp * 2048, (cid >> 5) * 1024 + nb * 256 + nh * 128 + ch * 64, mblk * 128 + mh * 64 + warp * 16);
                        asm volatile("cp.async.bulk.commit_group;" ::: "memory");
                    }
                }
                if (lane == 0) asm volatile("cp.async.bulk.wait_group.read 0;" ::: "memory");
            }
        }
    }
}

typedef CUresult (*EncodeFn)(CUtensorMap*, CUtensorMapDataType, cuuint32_t, void*, const cuuint64_t*, const cuuint64_t*, const cuuint32_t*,
                             const cuuint32_t*, CUtensorMapInterleave, CUtensorMapSwizzle, CUtensorMapL2promotion, CUtensorMapFloatOOBfill);

static void make_map(EncodeFn enc, CUtensorMap* m, const void* p, int cols, int rows, int bx, int by, CUtensorMapSwizzle sw) {
    cuuint64_t dims[2] = {(cuuint64_t)cols, (cuuint64_t)rows};
    cuuint64_t strides[1] = {(cuuint64_t)cols * 2};
    cuuint32_t box[2] = {(cuuint32_t)bx, (cuuint32_t)by};
    cuuint32_t es[2] = {1, 1};
    enc(m, CU_TENSOR_MAP_DATA_TYPE_BFLOAT16, 2, (void*)p, dims, strides, box, es, CU_TENSOR_MAP_INTERLEAVE_NONE, sw,
        CU_TENSOR_MAP_L2_PROMOTION_L2_64B, CU_TENSOR_MAP_FLOAT_OOB_FILL_NONE);
}

extern "C" void kernel_launch(void* const* d_in, const int* in_sizes, int n_in, void* d_out, int out_size) {
    (void)in_sizes; (void)n_in; (void)out_size;
    void* fn = nullptr;
    cudaDriverEntryPointQueryResult qr;
    cudaGetDriverEntryPoint("cuTensorMapEncodeTiled", &fn, cudaEnableDefault, &qr);
    EncodeFn enc = (EncodeFn)fn;
    void* pO = nullptr;
    cudaGetSymbolAddress(&pO, g_O);
    Maps mp;
    make_map(enc, &mp.XA, d_in[0], 1024, 2048, 64, 128, CU_TENSOR_MAP_SWIZZLE_128B);
    make_map(enc, &mp.Wq, d_in[1], 1024, 1024, 64, 64, CU_TENSOR_MAP_SWIZZLE_128B);
    make_map(enc, &mp.Wk, d_in[2], 32, 1024, 32, 64, CU_TENSOR_MAP_SWIZZLE_64B);
    make_map(enc, &mp.Wv, d_in[3], 32, 1024, 32, 64, CU_TENSOR_MAP_SWIZZLE_64B);
    make_map(enc, &mp.WoA, d_in[4], 1024, 1024, 64, 64, CU_TENSOR_MAP_SWIZZLE_128B);
    make_map(enc, &mp.XB, d_in[5], 1024, 2048, 64, 128, CU_TENSOR_MAP_SWIZZLE_128B);
    make_map(enc, &mp.Wqkv, d_in[6], 3072, 1024, 64, 64, CU_TENSOR_MAP_SWIZZLE_128B);
    make_map(enc, &mp.WoB, d_in[7], 1024, 1024, 64, 64, CU_TENSOR_MAP_SWIZZLE_128B);
    make_map(enc, &mp.O, pO, 1024, 4096, 64, 128, CU_TENSOR_MAP_SWIZZLE_128B);
    make_map(enc, &mp.Out, d_out, 2048, 2048, 64, 16, CU_TENSOR_MAP_SWIZZLE_128B);
    cudaFuncSetAttribute(mega_kernel, cudaFuncAttributeMaxDynamicSharedMemorySize, SMEM_BYTES);
    mega_kernel<<<132, 640, SMEM_BYTES, cudaStreamPerThread>>>(mp, 0);
}
```
